```python
import torch

def _softmax(x, axis=-1):
    return torch.softmax(x, dim=axis)

def _gelu(x):
    return torch.nn.functional.gelu(x, approximate='tanh')

def _silu(x):
    return torch.nn.functional.silu(x)

def _sigmoid(x):
    return torch.sigmoid(x)

def _layernorm(x, axis=-1, eps=1e-05):
    m = x.mean(dim=axis, keepdim=True)
    v = x.var(dim=axis, keepdim=True, unbiased=False)
    return (x - m) / torch.sqrt(v + eps)

def _scatter_add(tgt, idx, src, axis=0):
    return tgt.clone().index_add_(axis, idx, src)

def _segment_sum(src, seg, n):
    out = torch.zeros((n,) + src.shape[1:], dtype=src.dtype)
    return out.index_add_(0, seg, src)

def _pad(x, pw):
    flat = tuple((v for pair in reversed(pw) for v in pair))
    return torch.nn.functional.pad(x, flat)
kernel_name = 'standalone__video_video_swin__vision'

def setup_inputs():

    _w = lambda a: (lambda t: t.to(torch.bfloat16) if t.is_floating_point() else t)(torch.as_tensor(a))
    T = 4
    H = W = 512 // 7 * 7
    C, win = (96, 7)
    return {'x': _w((lambda *s: torch.randn(*s, dtype=torch.bfloat16) * 0.1)(1, T, H, W, C)), 'wqkv_t': _w((lambda *s: torch.randn(*s, dtype=torch.bfloat16) * 0.1)(C, 3 * C)), 'wo_t': _w((lambda *s: torch.randn(*s, dtype=torch.bfloat16) * 0.1)(C, C)), 'wqkv_s': _w((lambda *s: torch.randn(*s, dtype=torch.bfloat16) * 0.1)(C, 3 * C)), 'wo_s': _w((lambda *s: torch.randn(*s, dtype=torch.bfloat16) * 0.05)(C, C))}

def reference(x, wqkv_t, wo_t, wqkv_s, wo_s):
    B, T, H, W, C = x.shape
    win = 7
    scale = C ** (-0.5)
    h = _layernorm(x, axis=-1)
    ht = (lambda x, *d: x.permute(*d))(h, 0, 2, 3, 1, 4).reshape(B * H * W, T, C)
    qkv = ht @ wqkv_t
    q, k, v = (qkv[..., :C].clone(), qkv[..., C:2 * C].clone(), qkv[..., 2 * C:].clone())
    p = _softmax(torch.einsum('btc,bsc->bts', q, k) * scale, axis=-1)
    ot = torch.einsum('bts,bsc->btc', p, v) @ wo_t
    ot = (lambda x, *d: x.permute(*d))(ot.reshape(B, H, W, T, C), 0, 3, 1, 2, 4)
    x = x + ot
    h = _layernorm(x, axis=-1)
    nh, nw = (H // win, W // win)
    hs = h.reshape(B * T, nh, win, nw, win, C)
    hw = (lambda x, *d: x.permute(*d))(hs, 0, 1, 3, 2, 4, 5).reshape(B * T * nh * nw, win * win, C)
    qkv = hw @ wqkv_s
    q, k, v = (qkv[..., :C].clone(), qkv[..., C:2 * C].clone(), qkv[..., 2 * C:].clone())
    p = _softmax(torch.einsum('bqc,bkc->bqk', q, k) * scale, axis=-1)
    os = torch.einsum('bqk,bkc->bqc', p, v) @ wo_s
    os = (lambda x, *d: x.permute(*d))(os.reshape(B * T, nh, nw, win, win, C), 0, 1, 3, 2, 4, 5)
    os = os.reshape(B, T, H, W, C)
    return x + os
```

```cpp
#include <cuda_runtime.h>
#include <cuda.h>
#include <cuda_bf16.h>
#include <cuda_fp16.h>
#include <stdint.h>

#define LB 512
#define SF 21
#define SQA 0
#define TIE 5
#define SG 1
#define IL 1
#define RL 0
#define PT 0
#define PFT 0
#define PFS 0
#define FP 0
#define PF 0
#define ROLE 3
#define PERM 0
#define OV 1
#define LQ 0
#define LS 0
#define LIKELY(x) __builtin_expect(!!(x), 1)
#define UNLIKELY(x) __builtin_expect(!!(x), 0)
#define SP 1
#define RT 0
#define GB 0
#define G2 0
#define TL 1
namespace {

constexpr int kH = 511, kW = 511, kT = 4;
constexpr int kNWX = 73, kNWIN = 73 * 73;
constexpr int kChunk = 12544;
constexpr int kPlane = 3136;
constexpr int kXBytes = 37632;
constexpr int kBufStride = 38912;
constexpr int kWMat = 18432;
constexpr int kAtChunk = 104 * 64;
constexpr int kOffWt = 3 * kAtChunk;
constexpr int kOffAs = kOffWt + kWMat, kOffWs = kOffAs + kWMat;
constexpr int kWBytes = kOffWs + kWMat;
constexpr int kOffBuf = kWBytes;
constexpr int kOffBar = kOffBuf + 4 * kBufStride;
constexpr int kOffFlag = kOffBar + 96;
constexpr int kOffBarW = kOffBar + 112;
constexpr int kSmemBytes = kOffBar + 128;
constexpr int kNWG = 4;

struct Params {
  float cS_t, cS_s;
  float kt;
  float kappa;
};

__device__ uint4 g_wimg[kWBytes / 16];
__device__ __align__(16) Params g_par;

__device__ __forceinline__ uint32_t smem_u32(const void* p) { return (uint32_t)__cvta_generic_to_shared(p); }
__device__ __forceinline__ void mbar_init(uint32_t a, int c) { asm volatile("mbarrier.init.shared::cta.b64 [%0], %1;" ::"r"(a), "r"(c)); }
__device__ __forceinline__ void mbar_expect(uint32_t a, int bytes) {
  asm volatile("mbarrier.arrive.expect_tx.shared::cta.b64 _, [%0], %1;" ::"r"(a), "r"(bytes) : "memory");
}
__device__ __forceinline__ void mbar_arrive(uint32_t a) {
  asm volatile("mbarrier.arrive.shared::cta.b64 _, [%0];" ::"r"(a) : "memory");
}
__device__ __forceinline__ void mbar_wait(uint32_t a, uint32_t par) {
  asm volatile(
      "{\n.reg .pred p;\n.reg .u32 n;\n"
      "mbarrier.try_wait.parity.shared::cta.b64 p, [%0], %1;\n"
      "@p bra.uni WDONE;\n"
      "mov.u32 n, 0;\n"
      "WLOOP:\n"
      "mbarrier.try_wait.parity.shared::cta.b64 p, [%0], %1;\n"
      "@p bra.uni WDONE;\n"
      "add.u32 n, n, 1;\n"
      "setp.lt.u32 p, n, 0x1000000;\n"
      "@p bra.uni WLOOP;\n"
      "trap;\n"
      "WDONE:\n}" ::"r"(a), "r"(par) : "memory");
}
__device__ __forceinline__ bool mbar_test(uint32_t a, uint32_t par) {
  uint32_t r;
  asm volatile("{\n.reg .pred p;\nmbarrier.test_wait.parity.shared::cta.b64 p, [%1], %2;\nselp.u32 %0, 1, 0, p;\n}" : "=r"(r) : "r"(a), "r"(par) : "memory");
  return r != 0;
}
__device__ __forceinline__ void tma_load_win(uint32_t dst, const CUtensorMap* m, uint32_t bar, uint32_t w) {
  const uint32_t wy = (w * 57457u) >> 22, wx = w - wy * kNWX;
  asm volatile(
      "cp.async.bulk.tensor.5d.shared::cluster.global.mbarrier::complete_tx::bytes [%0], [%1, {%3,%4,%5,%3,%3}], [%2];" ::"r"(dst),
      "l"(m), "r"(bar), "r"(0), "r"(wx * 7), "r"(wy * 7)
      : "memory");
}
__device__ __forceinline__ void tma_prefetch_win(const CUtensorMap* m, uint32_t w) {
  const uint32_t wy = (w * 57457u) >> 22, wx = w - wy * kNWX;
  asm volatile("cp.async.bulk.prefetch.tensor.5d.L2.global [%0, {%1,%2,%3,%1,%1}];" ::"l"(m), "r"(0), "r"(wx * 7), "r"(wy * 7) : "memory");
}
__device__ __forceinline__ void wg_fence() { asm volatile("wgmma.fence.sync.aligned;" ::: "memory"); }
__device__ __forceinline__ void wg_commit() { asm volatile("wgmma.commit_group.sync.aligned;" ::: "memory"); }
template <int N>
__device__ __forceinline__ void wg_wait() { asm volatile("wgmma.wait_group.sync.aligned %0;" ::"n"(N) : "memory"); }
template <int N>
__device__ __forceinline__ void pin(uint32_t* d) {
#pragma unroll
  for (int i = 0; i < N; i++) asm volatile("" : "+r"(d[i])::"memory");
}
__device__ __forceinline__ void sched_fence(uint32_t a, uint32_t b, uint32_t c) {
  asm volatile("{\n.reg .pred p;\n.reg .b32 t;\nsetp.ne.u32 p, %0, 0x7fffffff;\n@p bra.uni SFD;\n"
               "add.u32 t, %1, %2;\nadd.u32 t, t, %3;\nnanosleep.u32 t;\nSFD:\n}" ::"r"(gridDim.x), "r"(a), "r"(b), "r"(c) : "memory");
}
__device__ __forceinline__ uint64_t mk_desc(uint32_t addr, uint32_t lbo16) {
  return ((uint64_t)0x80000020u << 32) | ((addr >> 4) & 0x3fff) | (lbo16 << 16);
}

#define R4(d, i) "+r"(d[i]), "+r"(d[i + 1]), "+r"(d[i + 2]), "+r"(d[i + 3])
#define O4(d, i) "=r"(d[i]), "=r"(d[i + 1]), "=r"(d[i + 2]), "=r"(d[i + 3])
#define D24 "{%0,%1,%2,%3,%4,%5,%6,%7,%8,%9,%10,%11,%12,%13,%14,%15,%16,%17,%18,%19,%20,%21,%22,%23},"
#define D14 "{%0,%1,%2,%3,%4,%5,%6,%7,%8,%9,%10,%11,%12,%13},"

template <int SC, int TB>
__device__ __forceinline__ void wg96h(uint32_t (&d)[24], const uint32_t* a, uint64_t db, uint32_t acc = 0) {
  if (SC == 2)
    asm volatile("{\n.reg .pred p;\nsetp.ne.u32 p, %30, 0;\n"
                 "wgmma.mma_async.sync.aligned.m64n96k16.f16.f16.f16 " D24 "{%24,%25,%26,%27}, %28, p, 1, 1, %29;\n}"
                 : R4(d, 0), R4(d, 4), R4(d, 8), R4(d, 12), R4(d, 16), R4(d, 20)
                 : "r"(a[0]), "r"(a[1]), "r"(a[2]), "r"(a[3]), "l"(db), "n"(TB), "r"(acc));
  else if (SC)
    asm volatile("wgmma.mma_async.sync.aligned.m64n96k16.f16.f16.f16 " D24 "{%24,%25,%26,%27}, %28, 1, 1, 1, %29;"
                 : R4(d, 0), R4(d, 4), R4(d, 8), R4(d, 12), R4(d, 16), R4(d, 20)
                 : "r"(a[0]), "r"(a[1]), "r"(a[2]), "r"(a[3]), "l"(db), "n"(TB));
  else
    asm volatile("wgmma.mma_async.sync.aligned.m64n96k16.f16.f16.f16 " D24 "{%24,%25,%26,%27}, %28, 0, 1, 1, %29;"
                 : O4(d, 0), O4(d, 4), O4(d, 8), O4(d, 12), O4(d, 16), O4(d, 20)
                 : "r"(a[0]), "r"(a[1]), "r"(a[2]), "r"(a[3]), "l"(db), "n"(TB));
}
template <int SC>
__device__ __forceinline__ void wg104h(uint32_t (&d)[26], const uint32_t* a, uint64_t db) {
  if (SC)
    asm volatile("wgmma.mma_async.sync.aligned.m64n104k16.f16.f16.f16 "
                 "{%0,%1,%2,%3,%4,%5,%6,%7,%8,%9,%10,%11,%12,%13,%14,%15,%16,%17,%18,%19,%20,%21,%22,%23,%24,%25},"
                 "{%26,%27,%28,%29}, %30, 1, 1, 1, 0;"
                 : R4(d, 0), R4(d, 4), R4(d, 8), R4(d, 12), R4(d, 16), R4(d, 20), "+r"(d[24]), "+r"(d[25])
                 : "r"(a[0]), "r"(a[1]), "r"(a[2]), "r"(a[3]), "l"(db));
  else
    asm volatile("wgmma.mma_async.sync.aligned.m64n104k16.f16.f16.f16 "
                 "{%0,%1,%2,%3,%4,%5,%6,%7,%8,%9,%10,%11,%12,%13,%14,%15,%16,%17,%18,%19,%20,%21,%22,%23,%24,%25},"
                 "{%26,%27,%28,%29}, %30, 0, 1, 1, 0;"
                 : O4(d, 0), O4(d, 4), O4(d, 8), O4(d, 12), O4(d, 16), O4(d, 20), "=r"(d[24]), "=r"(d[25])
                 : "r"(a[0]), "r"(a[1]), "r"(a[2]), "r"(a[3]), "l"(db));
}
template <int SC>
__device__ __forceinline__ void wg56h(uint32_t* d, const uint32_t* a, uint64_t db) {
  if (SC)
    asm volatile("wgmma.mma_async.sync.aligned.m64n56k16.f16.f16.f16 " D14 "{%14,%15,%16,%17}, %18, 1, 1, 1, 0;"
                 : R4(d, 0), R4(d, 4), R4(d, 8), "+r"(d[12]), "+r"(d[13])
                 : "r"(a[0]), "r"(a[1]), "r"(a[2]), "r"(a[3]), "l"(db));
  else
    asm volatile("wgmma.mma_async.sync.aligned.m64n56k16.f16.f16.f16 " D14 "{%14,%15,%16,%17}, %18, 0, 1, 1, 0;"
                 : O4(d, 0), O4(d, 4), O4(d, 8), "=r"(d[12]), "=r"(d[13])
                 : "r"(a[0]), "r"(a[1]), "r"(a[2]), "r"(a[3]), "l"(db));
}
template <int SC>
__device__ __forceinline__ void gemm_w(uint32_t (&d)[24], const uint32_t* a, uint64_t dw, uint32_t acc = 0) {
  wg_fence();
  wg96h<SC, 0>(d, a, dw, acc); wg96h<1, 0>(d, a + 4, dw + 2);
  wg96h<1, 0>(d, a + 8, dw + 384); wg96h<1, 0>(d, a + 12, dw + 386);
  wg96h<1, 0>(d, a + 16, dw + 768); wg96h<1, 0>(d, a + 20, dw + 770);
  wg_commit();
}
__device__ __forceinline__ void lds128(uint32_t* r, uint32_t a) {
  asm volatile("ld.shared.v4.b32 {%0,%1,%2,%3}, [%4];" : "=r"(r[0]), "=r"(r[1]), "=r"(r[2]), "=r"(r[3]) : "r"(a) : "memory");
}
__device__ __forceinline__ void ldsm4(uint32_t* r, uint32_t a) {
  asm volatile("ldmatrix.sync.aligned.m8n8.x4.shared.b16 {%0,%1,%2,%3}, [%4];"
               : "=r"(r[0]), "=r"(r[1]), "=r"(r[2]), "=r"(r[3]) : "r"(a) : "memory");
}
__device__ __forceinline__ void stsm4(uint32_t a, const uint32_t* r) {
  asm volatile("stmatrix.sync.aligned.m8n8.x4.shared.b16 [%0], {%1,%2,%3,%4};" ::"r"(a), "r"(r[0]), "r"(r[1]), "r"(r[2]), "r"(r[3])
               : "memory");
}
__device__ __forceinline__ uint32_t pack_h2(float lo, float hi) {
  uint32_t r; asm("cvt.rn.f16x2.f32 %0, %1, %2;" : "=r"(r) : "f"(hi), "f"(lo)); return r;
}
__device__ __forceinline__ uint32_t pack_h2_sat(float lo, float hi) {
  uint32_t r; asm("cvt.rn.satfinite.f16x2.f32 %0, %1, %2;" : "=r"(r) : "f"(hi), "f"(lo)); return r;
}
__device__ __forceinline__ uint32_t pack_bf2(float lo, float hi) {
  uint32_t r; asm("cvt.rn.bf16x2.f32 %0, %1, %2;" : "=r"(r) : "f"(hi), "f"(lo)); return r;
}
__device__ __forceinline__ __half2 as_h2(uint32_t v) { return *reinterpret_cast<__half2*>(&v); }
__device__ __forceinline__ uint32_t as_u(__half2 v) { return *reinterpret_cast<uint32_t*>(&v); }
__device__ __forceinline__ float2 unpack_h2(uint32_t v) { return __half22float2(as_h2(v)); }
__device__ __forceinline__ uint32_t h2ex2(uint32_t v) { uint32_t r; asm("ex2.approx.f16x2 %0, %1;" : "=r"(r) : "r"(v)); return r; }
__device__ __forceinline__ uint32_t h2max(uint32_t a, uint32_t b) { return as_u(__hmax2(as_h2(a), as_h2(b))); }
__device__ __forceinline__ uint32_t h2add(uint32_t a, uint32_t b) { return as_u(__hadd2(as_h2(a), as_h2(b))); }
__device__ __forceinline__ uint32_t h2sub(uint32_t a, uint32_t b) { return as_u(__hsub2(as_h2(a), as_h2(b))); }
__device__ __forceinline__ uint32_t h2mul(uint32_t a, uint32_t b) { return as_u(__hmul2(as_h2(a), as_h2(b))); }
__device__ __forceinline__ uint32_t h2fma(uint32_t a, uint32_t b, uint32_t c) { return as_u(__hfma2(as_h2(a), as_h2(b), as_h2(c))); }
__device__ __forceinline__ uint32_t lo2(uint32_t v) { return as_u(__low2half2(as_h2(v))); }
__device__ __forceinline__ uint32_t hi2(uint32_t v) { return as_u(__high2half2(as_h2(v))); }
__device__ __forceinline__ uint32_t fold_add(uint32_t a, uint32_t b) { return h2add(__byte_perm(a, b, 0x5410), __byte_perm(a, b, 0x7632)); }
__device__ __forceinline__ uint32_t bitsel(uint32_t a, uint32_t m, uint32_t c) {
  uint32_t r; asm("lop3.b32 %0, %1, %2, %3, 0xe2;" : "=r"(r) : "r"(a), "r"(m), "r"(c)); return r;
}
__device__ __forceinline__ float rcp_fast(float v) { float r; asm("rcp.approx.ftz.f32 %0, %1;" : "=f"(r) : "f"(v)); return r; }
__device__ __forceinline__ float rsq_fast(float v) { float r; asm("rsqrt.approx.ftz.f32 %0, %1;" : "=f"(r) : "f"(v)); return r; }
__device__ __forceinline__ float quad_sum(float v) {
  v += __shfl_xor_sync(0xffffffffu, v, 1);
  return v + __shfl_xor_sync(0xffffffffu, v, 2);
}
__device__ __forceinline__ uint32_t quad_h2add(uint32_t v) {
  v = h2add(v, __shfl_xor_sync(0xffffffffu, v, 1));
  return h2add(v, __shfl_xor_sync(0xffffffffu, v, 2));
}
__device__ __forceinline__ uint32_t score_scale(const float* p) { const float v = __ldcg(p); return pack_h2(v, v); }

constexpr float kEps96 = 1e-5f * 96.f * 96.f;
__device__ __forceinline__ float2 stat_f32(uint32_t e) {
  const float2 h = unpack_h2(e);
  return make_float2((e & 0x8000u) ? __uint_as_float((e << 16) & 0x7fff0000u) : h.x, (e & 0x8000u) ? __uint_as_float(e & 0xffff0000u) : h.y);
}

__device__ __forceinline__ uint32_t swz(uint32_t a) { return a ^ ((a >> 3) & 0x30); }
__device__ __forceinline__ uint32_t prmt(uint32_t a, uint32_t b, uint32_t s) {
  uint32_t r; asm("prmt.b32 %0, %1, %2, %3;" : "=r"(r) : "r"(a), "r"(b), "r"(s)); return r;
}
__device__ __forceinline__ void sched_fence6(uint32_t a, uint32_t b, uint32_t c, uint32_t d, uint32_t e, uint32_t f) {
  asm volatile("{\n.reg .pred p;\n.reg .b32 t;\nsetp.ne.u32 p, %0, 0x7fffffff;\n@p bra.uni SFD;\n"
               "add.u32 t, %1, %2;\nadd.u32 t, t, %3;\nadd.u32 t, t, %4;\nadd.u32 t, t, %5;\nadd.u32 t, t, %6;\nnanosleep.u32 t;\nSFD:\n}"
               ::"r"(gridDim.x), "r"(a), "r"(b), "r"(c), "r"(d), "r"(e), "r"(f) : "memory");
}
__device__ __forceinline__ void tie48(uint32_t* a, uint32_t* b, uint64_t d) {
  asm volatile("{\n.reg .pred p;\nsetp.ne.u32 p, %48, 0x7fffffff;\n@p bra.uni TIED;\nwgmma.fence.sync.aligned;\n"
               "wgmma.mma_async.sync.aligned.m64n192k16.f16.f16.f16 {%0,%1,%2,%3,%4,%5,%6,%7,%8,%9,%10,%11,%12,%13,%14,%15,%16,%17,%18,%19,%20,%21,%22,%23,%24,%25,%26,%27,%28,%29,%30,%31,%32,%33,%34,%35,%36,%37,%38,%39,%40,%41,%42,%43,%44,%45,%46,%47}, %49, %49, 1, 1, 1, 0, 0;\n"
               "wgmma.commit_group.sync.aligned;\nwgmma.wait_group.sync.aligned 0;\nTIED:\n}"
               : R4(a, 0), R4(a, 4), R4(a, 8), R4(a, 12), R4(a, 16), R4(a, 20), R4(b, 0), R4(b, 4), R4(b, 8), R4(b, 12), R4(b, 16), R4(b, 20)
               : "r"(gridDim.x), "l"(d) : "memory");
}
__device__ __forceinline__ void load_row(uint32_t* x, uint32_t la) {
  lds128(x, la); lds128(x + 4, (la ^ 32) + kChunk); lds128(x + 8, la + 2 * kChunk);
}
__device__ __forceinline__ uint32_t bf2_to_h2(uint32_t v) { return pack_h2(__uint_as_float(v << 16), __uint_as_float(v & 0xffff0000u)); }
__device__ __forceinline__ void gemm_at(uint32_t (&q)[26], const uint32_t* z, uint64_t da) {
  wg_fence();
  wg104h<0>(q, z, da); wg104h<1>(q, z + 4, da + 2);
  wg104h<1>(q, z + 8, da + 416); wg104h<1>(q, z + 12, da + 418);
  wg104h<1>(q, z + 16, da + 832); wg104h<1>(q, z + 20, da + 834);
  wg_commit();
}
__device__ __forceinline__ uint32_t sumsq(const uint32_t* z) {
  uint32_t q0[2], q1[2];
#pragma unroll
  for (int j = 0; j < 12; j++) {
    const uint32_t u = z[2 * j], v = z[2 * j + 1];
    q0[j & 1] = j < 2 ? h2mul(u, u) : h2fma(u, u, q0[j & 1]); q1[j & 1] = j < 2 ? h2mul(v, v) : h2fma(v, v, q1[j & 1]);
  }
  return fold_add(h2add(q0[0], q0[1]), h2add(q1[0], q1[1]));
}
__device__ __forceinline__ void scores_e(uint32_t* e, const uint32_t* q, const uint32_t* z) {
  uint32_t d[4];
#pragma unroll
  for (int j = 0; j < 12; j++) {
#pragma unroll
    for (int k = 0; k < 4; k++) d[k] = j ? h2fma(q[2 * j + (k >> 1)], z[2 * j + (k & 1)], d[k]) : h2mul(q[k >> 1], z[k & 1]);
  }
  e[0] = fold_add(d[0], d[2]); e[1] = fold_add(d[1], d[3]);
}
__device__ __forceinline__ uint32_t scores_r(const uint32_t* e, uint32_t selK) {
  return h2add(prmt(e[0], e[1], selK), __shfl_xor_sync(0xffffffffu, prmt(e[0], e[1], selK ^ 0x2222u), 1));
}
__device__ __forceinline__ uint32_t scores(const uint32_t* q, const uint32_t* z, uint32_t selK) {
  uint32_t e[2];
  scores_e(e, q, z);
  return scores_r(e, selK);
}
__device__ __forceinline__ float2 rstd(float2 d) { return make_float2(rsq_fast(fmaf(d.x, 1.f / 96.f, 1e-5f)), rsq_fast(fmaf(d.y, 1.f / 96.f, 1e-5f))); }
__device__ __forceinline__ void ln1_f32(uint32_t* z, uint32_t la0, uint32_t la1, float* ie, float* m) {
  float acc[48];
  uint32_t x0[12], x1[12];
  load_row(x0, la0); load_row(x1, la1);
#pragma unroll
  for (int j = 0; j < 12; j++) {
    acc[4 * j] = __uint_as_float(x0[j] << 16); acc[4 * j + 1] = __uint_as_float(x0[j] & 0xffff0000u);
    acc[4 * j + 2] = __uint_as_float(x1[j] << 16); acc[4 * j + 3] = __uint_as_float(x1[j] & 0xffff0000u);
  }
  float s[4], q[4];
#pragma unroll
  for (int e = 0; e < 4; e++) { s[e] = acc[e]; q[e] = acc[e] * acc[e]; }
#pragma unroll
  for (int j = 4; j < 48; j++) { s[j & 3] += acc[j]; q[j & 3] = fmaf(acc[j], acc[j], q[j & 3]); }
  const float s0 = quad_sum(s[0] + s[1]), s1 = quad_sum(s[2] + s[3]), q0 = quad_sum(q[0] + q[1]), q1 = quad_sum(q[2] + q[3]);
  const float u0 = rsq_fast(fmaxf(fmaf(-s0, s0, fmaf(q0, 96.f, kEps96)), kEps96));
  const float u1 = rsq_fast(fmaxf(fmaf(-s1, s1, fmaf(q1, 96.f, kEps96)), kEps96));
  const float n0 = -s0 * u0, n1 = -s1 * u1;
  ie[0] = 96.f * u0; ie[1] = 96.f * u1;
  m[0] = s0 * (1.f / 96.f); m[1] = s1 * (1.f / 96.f);
#pragma unroll
  for (int j = 0; j < 12; j++) {
    z[2 * j] = pack_h2(fmaf(acc[4 * j], ie[0], n0), fmaf(acc[4 * j + 1], ie[0], n0));
    z[2 * j + 1] = pack_h2(fmaf(acc[4 * j + 2], ie[1], n1), fmaf(acc[4 * j + 3], ie[1], n1));
  }
}
__device__ __forceinline__ float2 sumsq_f32(const uint32_t* z) {
  float2 qq = make_float2(0.f, 0.f);
#pragma unroll
  for (int j = 0; j < 12; j++) {
    const float2 u = unpack_h2(z[2 * j]), v = unpack_h2(z[2 * j + 1]);
    qq.x = fmaf(u.x, u.x, fmaf(u.y, u.y, qq.x)); qq.y = fmaf(v.x, v.x, fmaf(v.y, v.y, qq.y));
  }
  return make_float2(quad_sum(qq.x), quad_sum(qq.y));
}
__device__ __forceinline__ float2 var96_f32(const uint32_t* z, uint32_t my) {
  const float2 q = sumsq_f32(z), m = unpack_h2(my);
  return make_float2(fmaf(-96.f * m.x, m.x, q.x), fmaf(-96.f * m.y, m.y, q.y));
}
__device__ __forceinline__ void store_tile(const uint32_t* h, uint32_t ma) {
  const uint32_t mb = ma ^ 32;
  stsm4(ma, h); stsm4(mb, h + 4);
  stsm4(mb + kChunk, h + 8); stsm4(ma + kChunk, h + 12);
  stsm4(ma + 2 * kChunk, h + 16); stsm4(mb + 2 * kChunk, h + 20);
}
__device__ __forceinline__ void ln2(uint32_t* h, uint32_t rr, uint32_t my, uint32_t ma) {
  const uint32_t nn = as_u(__hmul2(__hneg2(as_h2(my)), as_h2(rr)));
#pragma unroll
  for (int j = 0; j < 12; j++) { h[2 * j] = h2fma(h[2 * j], lo2(rr), lo2(nn)); h[2 * j + 1] = h2fma(h[2 * j + 1], hi2(rr), hi2(nn)); }
  store_tile(h, ma);
}

struct TAddr {
  uint32_t a0;
  uint32_t i0;
  int ow;
};
__device__ __forceinline__ TAddr t_addr(uint32_t sb, uint32_t p0, int lane) {
  TAddr r;
  r.i0 = (p0 * 21400u) >> 20;
  r.ow = p0 - 49 * r.i0;
  const uint32_t ia = r.i0 & 3, ib = (r.i0 + 1) & 3;
  r.a0 = sb + kOffBuf + ia * kBufStride + r.ow * 64 + lane * 16;
  if (lane >= 4 * (49 - r.ow)) r.a0 += (ib - ia) * kBufStride - kPlane;
  return r;
}
__device__ __forceinline__ void t_out_addr(uint32_t sb, const TAddr& a, int lane, uint32_t& m0, uint32_t& sa) {
  const uint32_t ia = a.i0 & 3, ib = (a.i0 + 1) & 3;
  const uint32_t bufA = sb + kOffBuf + ia * kBufStride, dB = (ib - ia) * kBufStride;
  sa = bufA + kXBytes + a.ow * 16 + lane * 4;
  if (lane >= 4 * (49 - a.ow)) sa += dB - 49 * 16;
  m0 = bufA + a.ow * 64 + ((lane & 7) * 64 + ((lane >> 3) & 1) * kPlane + (lane & 16));
  if ((lane & 7) >= 49 - a.ow) m0 += dB - kPlane;
}
__device__ __forceinline__ void load_tile(uint32_t* x, uint32_t a) { load_row(x, swz(a)); load_row(x + 12, swz(a + kPlane)); }
template <int N>
__device__ __forceinline__ void clear(uint32_t* x) {
#pragma unroll
  for (int j = 0; j < N; j++) asm volatile("mov.b32 %0, 0;" : "=r"(x[j]));
}
template <bool kDirect>
__device__ __forceinline__ void softmax4(uint32_t* s, uint32_t rhoA, uint32_t rhoB, uint32_t ro, float f) {
  if (kDirect) { s[0] = h2mul(s[0], rhoA); s[1] = h2mul(s[1], rhoB); }
  uint32_t mx = h2max(s[0], s[1]);
  mx = h2max(lo2(mx), hi2(mx));
  if (kDirect) {
    const uint32_t nm = as_u(__hmul2(__hneg2(as_h2(mx)), as_h2(ro)));
    s[0] = h2fma(s[0], ro, nm); s[1] = h2fma(s[1], ro, nm);
  } else {
    s[0] = h2mul(h2sub(s[0], mx), ro); s[1] = h2mul(h2sub(s[1], mx), ro);
  }
  s[0] = h2ex2(s[0]); s[1] = h2ex2(s[1]);
  uint32_t sm = h2add(s[0], s[1]);
  sm = h2add(lo2(sm), hi2(sm));
  const float iv = f * rcp_fast(__low2float(as_h2(sm)));
  const uint32_t inv = pack_h2(iv, iv);
  if (kDirect) { s[0] = h2mul(h2mul(s[0], rhoA), inv); s[1] = h2mul(h2mul(s[1], rhoB), inv); }
  else { s[0] = h2mul(s[0], inv); s[1] = h2mul(s[1], inv); }
}
template <bool kFirst>
__device__ __forceinline__ void mix(uint32_t* u, const uint32_t* z, uint32_t p0, uint32_t p1) {
#pragma unroll
  for (int j = 0; j < 12; j++) {
    u[2 * j] = h2fma(z[2 * j + 1], hi2(p0), kFirst ? h2mul(z[2 * j], lo2(p0)) : h2fma(z[2 * j], lo2(p0), u[2 * j]));
    u[2 * j + 1] = h2fma(z[2 * j + 1], hi2(p1), kFirst ? h2mul(z[2 * j], lo2(p1)) : h2fma(z[2 * j], lo2(p1), u[2 * j + 1]));
  }
}
__device__ __forceinline__ void put_stats(uint32_t sa, float sg, float mm, const Params& P) {
  const bool ok = (sg >= fmaxf(0.0045f, P.kappa * 0.011f)) & (fmaf(sg, 9.8f, fabsf(mm)) < fmaf(P.kappa, -627.2f, 60000.f));
  const uint32_t sh = pack_h2(sg, mm), sw = pack_bf2(-sg, mm);
  asm volatile("st.shared.b32 [%0], %1;" ::"r"(sa), "r"(ok ? sh : sw) : "memory");
}

__device__ __forceinline__ bool task_T(uint32_t sb, const TAddr& a, bool dead, uint32_t flag, int lane, const Params& P) {
  const int c = lane & 3;
  const uint32_t selK = (c & 1) ? 0x7632u : 0x5410u, selO = 0x1010u + c * 0x2222u;
  const uint64_t da = mk_desc(sb, 1), dw = mk_desc(sb + kOffWt, 1);
  uint32_t x[48], yA[24], yB[24], qA[26], qB[26], ssA, ssB, m0, sa;
  load_tile(x, a.a0); load_tile(x + 24, a.a0 + 2 * kPlane);
#pragma unroll
  for (int j = 0; j < 12; j++) { yA[2 * j] = bf2_to_h2(x[j]); yA[2 * j + 1] = bf2_to_h2(x[12 + j]); }
#pragma unroll
  for (int j = 0; j < 12; j++) { yB[2 * j] = bf2_to_h2(x[24 + j]); yB[2 * j + 1] = bf2_to_h2(x[36 + j]); }
  ssB = sumsq(yB);
  ssA = sumsq(yA);
  gemm_at(qA, yA, da);
  gemm_at(qB, yB, da);
  ssB = quad_h2add(ssB);
  ssA = quad_h2add(ssA);
  uint32_t rA[2], rB[2];
  wg_wait<1>(); pin<26>(qA);
  const uint32_t myA = __byte_perm(qA[24], qA[25], 0x5410), nuA = __byte_perm(qA[24], qA[25], 0x7632);
  const uint32_t nsA = h2mul(myA, 0xd600d600u);
  const float2 ra = rstd(unpack_h2(h2fma(nsA, myA, ssA)));
  const uint32_t rhoA = pack_h2(ra.x, ra.y);
  rA[0] = scores(qA, yA, selK);
  sched_fence(rA[0], rhoA, 0);
  wg_wait<0>(); pin<26>(qB);
  const uint32_t myB = __byte_perm(qB[24], qB[25], 0x5410), nuB = __byte_perm(qB[24], qB[25], 0x7632);
  const uint32_t nsB = h2mul(myB, 0xd600d600u);
  const float2 rb = rstd(unpack_h2(h2fma(nsB, myB, ssB)));
  const uint32_t rhoB = pack_h2(rb.x, rb.y);
  const uint32_t ro = prmt(rhoA, rhoB, selO), mo = bitsel(prmt(myA, myB, selO), 0xffffu, 0x292e0000u);
  const bool fine = __hble2(__habs2(as_h2(h2fma(ro, mo, 0xbc190000u))), as_h2(0x3c003c00u));
  asm volatile("{\n.reg .pred p;\nsetp.ne.u32 p, %1, 0;\n@p st.volatile.shared.b32 [%0], %1;\n}" ::"r"(flag), "r"((uint32_t)(!fine & !dead)) : "memory");
  uint32_t mu;
  rA[1] = scores(qA, yB, selK); rB[0] = scores(qB, yA, selK); rB[1] = scores(qB, yB, selK);
  uint32_t p[8], s[2];
#pragma unroll
  for (int k = 0; k < 2; k++) s[k] = h2add((c & 2) ? rB[k] : rA[k], __shfl_xor_sync(0xffffffffu, (c & 2) ? rA[k] : rB[k], 2));
  softmax4<true>(s, rhoA, rhoB, ro, P.kt);
#pragma unroll
  for (int t = 0; t < 4; t++) { p[2 * t] = __shfl_sync(0xffffffffu, s[0], t, 4); p[2 * t + 1] = __shfl_sync(0xffffffffu, s[1], t, 4); }
  mu = h2fma(s[1], nuB, h2mul(s[0], nuA));
  mix<true>(qA, yA, p[0], p[2]);
  if (!G2) mix<false>(qA, yB, p[1], p[3]);
  mu = h2add(lo2(mu), hi2(mu));
  mix<true>(qB, yA, p[4], p[6]);
  tie48(yA, yB, dw);
  gemm_w<1>(yA, qA, dw);
  sched_fence(0, 0, 0);
  mix<false>(qB, yB, p[5], p[7]);
  gemm_w<1>(yB, qB, dw);
  t_out_addr(sb, a, lane, m0, sa);
  wg_wait<1>(); pin<24>(yA);
  uint32_t bad;
  asm volatile("ld.shared.b32 %0, [%1];" : "=r"(bad) : "r"(flag + (yA[0] & (gridDim.x == 0x7fffffffu))) : "memory");
  float2 d = unpack_h2(h2fma(nsA, myA, quad_h2add(sumsq(yA))));
  if (UNLIKELY(__any_sync(0xffffffffu, !(d.x + d.y < 65000.f) | (bad != 0)))) {
    if (__any_sync(0xffffffffu, bad != 0)) {
      wg_wait<0>(); pin<24>(yB);
      return false;
    }
    d = var96_f32(yA, myA);
  }
  float2 r = rstd(make_float2(fabsf(d.x), fabsf(d.y)));
  const uint32_t rrA = pack_h2(r.x, r.y);
  ln2(yA, rrA, myA, swz(m0));
  sched_fence(0, 0, 0);
  wg_wait<0>(); pin<24>(yB);
  d = unpack_h2(h2fma(nsB, myB, quad_h2add(sumsq(yB))));
  if (UNLIKELY(__any_sync(0xffffffffu, !(d.x + d.y < 65000.f)))) d = var96_f32(yB, myB);
  r = rstd(make_float2(fabsf(d.x), fabsf(d.y)));
  const uint32_t rrB = pack_h2(r.x, r.y);
  ln2(yB, rrB, myB, swz(m0 + 2 * kPlane));
  put_stats(sa, rcp_fast(__low2float(as_h2(prmt(rrA, rrB, selO)))), __low2float(as_h2(h2add(mo, mu))), P);
  return true;
}

__device__ __forceinline__ void task_T_general(uint32_t sb, uint32_t p0, const Params& P) {
  int lane;
  asm volatile("mov.u32 %0, %%laneid;" : "=r"(lane));
  const int c = lane & 3;
  const uint64_t da = mk_desc(sb, 1), dw = mk_desc(sb + kOffWt, 1);
  uint32_t yA[24], yB[24], qA[26], qB[26];
  float ieo, mo, ao;
  {
    float ie[4], m[4];
    const uint32_t a0 = t_addr(sb, p0, lane).a0;
    ln1_f32(yA, swz(a0), swz(a0 + kPlane), ie, m);
    ln1_f32(yB, swz(a0 + 2 * kPlane), swz(a0 + 3 * kPlane), ie + 2, m + 2);
    const float2 na = sumsq_f32(yA), nb = sumsq_f32(yB);
    const float ik = 9.8f * rcp_fast(P.kt) * rsq_fast(fmaxf(fmaxf(fmaxf(na.x, na.y), fmaxf(nb.x, nb.y)), 2e-7f));
    ieo = (c & 2) ? ((c & 1) ? ie[3] : ie[2]) : ((c & 1) ? ie[1] : ie[0]);
    mo = (c & 2) ? ((c & 1) ? m[3] : m[2]) : ((c & 1) ? m[1] : m[0]);
    const bool lim = (ieo * P.kt > 400.f) & (ik < ieo);
    const float u = ik * rcp_fast(ieo);
    ao = lim ? u : 1.f; ieo = lim ? ik : ieo;
  }
  uint32_t rA[2], rB[2], s[2], p[8];
  const uint32_t selK = (c & 1) ? 0x7632u : 0x5410u;
  gemm_at(qA, yA, da);
  wg_wait<0>(); pin<26>(qA);
  const uint32_t nuA = __byte_perm(qA[24], qA[25], 0x7632);
  rA[0] = scores(qA, yA, selK); rA[1] = scores(qA, yB, selK);
  sched_fence(rA[0], rA[1], nuA);
  gemm_at(qB, yB, da);
  wg_wait<0>(); pin<26>(qB);
  const uint32_t nuB = __byte_perm(qB[24], qB[25], 0x7632);
  rB[0] = scores(qB, yA, selK); rB[1] = scores(qB, yB, selK);
#pragma unroll
  for (int k = 0; k < 2; k++) s[k] = h2add((c & 2) ? rB[k] : rA[k], __shfl_xor_sync(0xffffffffu, (c & 2) ? rA[k] : rB[k], 2));
  softmax4<false>(s, 0, 0, score_scale(&g_par.cS_t), P.kt * ieo);
  uint32_t mu = h2fma(s[1], nuB, h2mul(s[0], nuA));
  mu = h2add(lo2(mu), hi2(mu));
#pragma unroll
  for (int t = 0; t < 4; t++) { p[2 * t] = __shfl_sync(0xffffffffu, s[0], t, 4); p[2 * t + 1] = __shfl_sync(0xffffffffu, s[1], t, 4); }
  sched_fence(mu, 0, 0);
  mix<true>(qA, yA, p[0], p[2]); mix<false>(qA, yB, p[1], p[3]);
  mix<true>(qB, yA, p[4], p[6]); mix<false>(qB, yB, p[5], p[7]);
  const uint32_t ah = pack_h2(ao, ao);
#pragma unroll
  for (int t = 0; t < 4; t++) {
    const uint32_t a = __shfl_sync(0xffffffffu, ah, t, 4);
#pragma unroll
    for (int j = 0; j < 12; j++) asm volatile("mul.f16x2 %0, %0, %1;" : "+r"(((t & 2) ? yB : yA)[2 * j + (t & 1)]) : "r"(a));
  }
  gemm_w<1>(yA, qA, dw);
  gemm_w<1>(yB, qB, dw);
  wg_wait<0>(); pin<24>(yA); pin<24>(yB);
  asm volatile("mov.u32 %0, %%laneid;" : "=r"(lane));
  uint32_t m0, sa;
  t_out_addr(sb, t_addr(sb, p0, lane), lane, m0, sa);
  float ie[4];
#pragma unroll
  for (int t = 0; t < 4; t++) ie[t] = __shfl_sync(0xffffffffu, ieo, t, 4);
  const float2 da2 = sumsq_f32(yA), db2 = sumsq_f32(yB);
  const uint32_t rrA = pack_h2_sat(rsq_fast(fmaf(da2.x, 1.f / 96.f, 1e-5f * ie[0] * ie[0])), rsq_fast(fmaf(da2.y, 1.f / 96.f, 1e-5f * ie[1] * ie[1])));
  const uint32_t rrB = pack_h2_sat(rsq_fast(fmaf(db2.x, 1.f / 96.f, 1e-5f * ie[2] * ie[2])), rsq_fast(fmaf(db2.y, 1.f / 96.f, 1e-5f * ie[3] * ie[3])));
  ln2(yA, rrA, 0u, swz(m0)); ln2(yB, rrB, 0u, swz(m0 + 2 * kPlane));
  const float r = __low2float(as_h2(prmt(rrA, rrB, 0x1010u + (lane & 3) * 0x2222u))), sg = rcp_fast(r * ieo);
  put_stats(sa, sg, fmaf(__low2float(as_h2(mu)) * r, sg, mo), P);
}

__device__ __forceinline__ void t_release(uint32_t sb, const TAddr& a, int lane) {
  const uint32_t barD = sb + kOffBar + 32;
  asm volatile("fence.proxy.async.shared::cta;" ::: "memory");
  __syncwarp();
  asm volatile("{\n.reg .pred p, q;\nsetp.eq.u32 p, %2, 0;\nsetp.ge.and.s32 q, %3, 42, p;\n"
               "@p mbarrier.arrive.shared::cta.b64 _, [%0];\n@q mbarrier.arrive.shared::cta.b64 _, [%1];\n}"
               ::"r"(barD + (a.i0 & 3) * 8), "r"(barD + ((a.i0 + 1) & 3) * 8), "r"(lane), "r"(a.ow) : "memory");
}
__device__ __forceinline__ void loop_T(uint32_t sb, int nw, int wg, int wp, int lane, const Params& P, bool direct) {
  const uint32_t barF = sb + kOffBar, flag = sb + kOffFlag + wg * 4;
  const uint32_t pend = 49 * nw + 8 * wp;
  mbar_wait(sb + kOffBarW, 0);
  for (uint32_t p0 = 32 * wg + 8 * wp; p0 < pend; p0 += 64) {
    const TAddr a = t_addr(sb, p0, lane);
    mbar_wait(barF + (a.i0 & 3) * 8, (a.i0 >> 2) & 1);
    if (UNLIKELY(a.ow >= 42)) mbar_wait(barF + ((a.i0 + 1) & 3) * 8, ((a.i0 + 1) >> 2) & 1);
    if (LIKELY(direct)) {
      if (LIKELY(task_T(sb, a, a.i0 + (lane >= 4 * (49 - a.ow)) == nw, flag, lane, P))) {
        t_release(sb, a, lane);
        continue;
      }
      asm volatile("barrier.cta.sync.aligned %0, 128;" ::"r"(wg + 1) : "memory");
      asm volatile("st.shared.b32 [%0], %1;\nfence.acq_rel.cta;" ::"r"(flag), "r"(0) : "memory");
    }
    task_T_general(sb, p0, P);
    t_release(sb, a, lane);
  }
}

struct SFrame {
  uint32_t ma;
  uint32_t o0, o1;
  uint32_t pl;
  uint32_t st;
  bool light;
};
__device__ __forceinline__ SFrame s_frame(int t, int wp, int lane) {
  SFrame f;
  const int rb = (wp + t) & 3;
  f.light = rb == 3;
  f.pl = t * kPlane;
  f.st = kXBytes + rb * 256 + t * 4;
  f.ma = f.light && (lane & 15) ? kXBytes + 1024 : swz(t * kPlane + rb * 1024 + ((lane * 65) & 0x3d0));
  const uint32_t r = 16 * rb + (lane >> 2);
  f.o0 = (t * (kH * kW) + r + (r / 7) * (kW - 7)) * 192 + (lane & 3) * 16;
  f.o1 = (t * (kH * kW) + r + 8 + ((r + 8) / 7) * (kW - 7)) * 192 + (lane & 3) * 16;
  asm volatile("" : "+r"(f.ma), "+r"(f.o0), "+r"(f.o1));
  return f;
}
__device__ __forceinline__ void s_load(uint32_t (&v)[24], uint32_t buf, const SFrame& f) {
  uint32_t a0 = f.ma;
  asm volatile("" : "+r"(a0));
  const uint32_t st = a0 >= kXBytes ? 0 : kChunk, a1 = a0 + st, a2 = a1 + st;
  ldsm4(v, buf + a0); ldsm4(v + 4, buf + (a0 ^ 32));
  ldsm4(v + 8, buf + (a1 ^ 32)); ldsm4(v + 12, buf + a1);
  ldsm4(v + 16, buf + a2); ldsm4(v + 20, buf + (a2 ^ 32));
}
__device__ __forceinline__ void gemm_s(uint32_t* s, const uint32_t* q, uint32_t pl) {
  const uint64_t dA = mk_desc(pl, 1);
  wg_fence();
  wg56h<0>(s, q, dA); wg56h<1>(s, q + 4, dA + 2);
  wg56h<1>(s, q + 8, dA + 784); wg56h<1>(s, q + 12, dA + 786);
  wg56h<1>(s, q + 16, dA + 1568); wg56h<1>(s, q + 20, dA + 1570);
  wg_commit();
}
template <bool kAll>
__device__ __forceinline__ void stg128(uint8_t* o, const uint32_t* w, uint32_t doit) {
  if (kAll) asm volatile("st.global.v4.b32 [%0], {%1,%2,%3,%4};" ::"l"(o), "r"(w[0]), "r"(w[1]), "r"(w[2]), "r"(w[3]) : "memory");
  else asm volatile("{\n.reg .pred p;\nsetp.ne.u32 p, %5, 0;\n@p st.global.v4.b32 [%0], {%1,%2,%3,%4};\n}" ::"l"(o), "r"(w[0]), "r"(w[1]), "r"(w[2]), "r"(w[3]), "r"(doit) : "memory");
}
template <int kRow, bool kAll>
__device__ __forceinline__ void s_store(const uint32_t (&v)[24], uint32_t e, uint8_t* o) {
  uint32_t w[12];
#pragma unroll
  for (int j = 0; j < 12; j++) { const float2 y = unpack_h2(h2fma(v[2 * j + kRow], lo2(e), hi2(e))); w[j] = pack_bf2(y.x, y.y); }
#pragma unroll
  for (int i3 = 0; i3 < 3; i3++) stg128<kAll>(o + 64 * i3, w + 4 * i3, e);
}
template <int kRow, bool kAdd>
__device__ __forceinline__ void s_store_wide(const uint32_t (&v)[24], uint32_t e, uint8_t* o, const Params& P) {
  const float2 z = stat_f32(e);
#pragma unroll
  for (int i3 = 0; i3 < 3; i3++) {
    uint32_t w[4] = {0, 0, 0, 0};
    if (kAdd)
      asm volatile("{\n.reg .pred p;\nsetp.ne.u32 p, %5, 0;\n@p ld.global.v4.b32 {%0,%1,%2,%3}, [%4];\n}"
                   : "+r"(w[0]), "+r"(w[1]), "+r"(w[2]), "+r"(w[3]) : "l"(o + 64 * i3), "r"(e) : "memory");
#pragma unroll
    for (int j = 0; j < 4; j++) {
      const float2 y = unpack_h2(v[8 * i3 + 2 * j + kRow]);
      w[j] = kAdd ? pack_bf2(fmaf(y.x, P.kappa, __uint_as_float(w[j] << 16)), fmaf(y.y, P.kappa, __uint_as_float(w[j] & 0xffff0000u)))
                  : pack_bf2(fmaf(y.x, z.x, z.y), fmaf(y.y, z.x, z.y));
    }
    stg128<false>(o + 64 * i3, w, e);
  }
  __syncwarp();
}
__device__ __forceinline__ uint32_t ex2_pair(uint32_t s) {
  uint32_t lo, hi;
  asm volatile("{\n.reg .b16 a, b, c;\nmov.b32 {a, b}, %2;\nex2.approx.f16 c, a;\ncvt.u32.u16 %0, c;\nex2.approx.f16 c, b;\ncvt.u32.u16 %1, c;\n}"
               : "=r"(lo), "=r"(hi) : "r"(s));
  return lo + hi * 65536u;
}
__device__ __forceinline__ uint32_t ex2_lo(uint32_t s) {
  uint32_t lo;
  asm volatile("{\n.reg .b16 a, b, c;\nmov.b32 {a, b}, %1;\nex2.approx.f16 c, a;\ncvt.u32.u16 %0, c;\n}" : "=r"(lo) : "r"(s));
  return lo;
}

template <int kSecond>
__device__ __forceinline__ void step_S(uint32_t sb, uint32_t (&v)[24], uint32_t (&vn)[24], uint32_t (&q)[24], uint32_t (&s)[16], const SFrame& f,
                                       const SFrame& fn, uint32_t i, int nw, uint32_t w, uint32_t wlast, uint8_t* ob, int lane, const Params& P,
                                       bool scaled, const CUtensorMap* tm) {
  const uint32_t ia = i & 3, ib = kSecond ? (i + 1) & 3 : ia;
  const uint32_t buf = sb + kOffBuf + ia * kBufStride, bufn = sb + kOffBuf + ib * kBufStride;
  const uint64_t dQ = mk_desc(sb + kOffAs, 1);
  const uint32_t never = gridDim.x == 0x7fffffffu;
  uint32_t p[16], u[24], e0, e1;
  const uint32_t sta = buf + f.st + (lane & 0x1c) * 4;
  asm volatile("ld.shared.b32 %0, [%1];" : "=r"(e0) : "r"(sta) : "memory");
  asm volatile("ld.shared.b32 %0, [%1];" : "=r"(e1) : "r"(sta + 128) : "memory");
  const uint32_t keep = (lane & 3) == 0 ? 0x0000ffffu : 0u;
  s[12] = bitsel(s[12], keep, 0xfc00fc00u); s[13] = bitsel(s[13], keep, 0xfc00fc00u);
  __half2 am = __hmax2(as_h2(s[12]), as_h2(s[13])), an = __hmax2(__habs2(as_h2(s[0])), __habs2(as_h2(s[1])));
#pragma unroll
  for (int j = 2; j < 7; j++) { am = __hmax2(am, __habs2(as_h2(s[j]))); an = __hmax2(an, __habs2(as_h2(s[j + 5]))); }
  bool ok = __hble2(__hmax2(am, an), as_h2(0x47004700u)) & !scaled;
  constexpr int kE = IL == 0 ? 12 : IL == 1 ? 4 : IL == 2 ? 0 : 8;
  p[12] = ex2_lo(s[12]); p[13] = ex2_lo(s[13]);
#pragma unroll
  for (int j = 0; j < kE; j++) p[j] = ex2_pair(s[j]);
  if (UNLIKELY(!__all_sync(0xffffffffu, ok))) {
    const uint32_t x0 = h2max(h2max(h2max(s[0], s[2]), h2max(s[4], s[6])), h2max(h2max(s[8], s[10]), s[12]));
    const uint32_t x1 = h2max(h2max(h2max(s[1], s[3]), h2max(s[5], s[7])), h2max(h2max(s[9], s[11]), s[13]));
    uint32_t mx = h2max(__byte_perm(x0, x1, 0x5410), __byte_perm(x0, x1, 0x7632));
    mx = h2max(mx, __shfl_xor_sync(0xffffffffu, mx, 1));
    mx = h2max(mx, __shfl_xor_sync(0xffffffffu, mx, 2));
    const uint32_t cs = score_scale(&g_par.cS_s);
#pragma unroll
    for (int j = 0; j < 7; j++) { s[2 * j] = h2mul(h2sub(s[2 * j], lo2(mx)), cs); s[2 * j + 1] = h2mul(h2sub(s[2 * j + 1], hi2(mx)), cs); }
    p[12] = ex2_lo(s[12]); p[13] = ex2_lo(s[13]);
#pragma unroll
    for (int j = 0; j < kE; j++) p[j] = ex2_pair(s[j]);
    ok = !never;
  }
  asm volatile("mov.b32 %0, 0;\nmov.b32 %1, 0;" : "=r"(p[14]), "=r"(p[15]));
  const uint64_t mn = mk_desc(buf + f.pl, kChunk >> 4);
  wg_fence();
  wg96h<2, 1>(q, p + 12, mn + 192, never); wg96h<1, 1>(q, p, mn);
#pragma unroll
  for (int j = 4; j < 12; j++) p[j] = ex2_pair(s[j]);
  const bool wide = __any_sync(0xffffffffu, ((e0 | e1) & 0x8000u) != 0u);
  uint32_t rs = fold_add(h2add(h2add(h2add(p[0], p[2]), p[12]), h2add(h2add(p[4], p[6]), h2add(p[8], p[10]))),
                         h2add(h2add(h2add(p[1], p[3]), p[13]), h2add(h2add(p[5], p[7]), h2add(p[9], p[11])))), rt;
  asm volatile("shfl.sync.bfly.b32 %0, %1, 1, 31, 0xffffffff;" : "=r"(rt) : "r"(rs));
  wg_fence();
  wg96h<1, 1>(q, p + 4, mn + 64); wg96h<1, 1>(q, p + 8, mn + 128);
  wg_commit();
  if (UNLIKELY(wide)) { s_store_wide<0, false>(v, e0, ob + f.o0, P); s_store_wide<1, false>(v, e1, ob + f.o1, P); }
  rs = h2add(rs, rt);
  asm volatile("shfl.sync.bfly.b32 %0, %1, 2, 31, 0xffffffff;" : "=r"(rt) : "r"(rs));
  const uint32_t barN = sb + kOffBar + 32 + ib * 8, parN = ((i + 1) >> 2) & 1;
  bool have = !kSecond && LQ == 0;
  if (have) s_load(vn, bufn, fn);
  rs = h2add(rs, rt);
  const float d0 = __low2float(as_h2(rs)), d1 = __high2float(as_h2(rs));
  const float g0 = wide ? P.kappa : __low2float(as_h2(e0)), g1 = wide ? P.kappa : __low2float(as_h2(e1));
  const float c0 = P.kappa * rcp_fast(d0 * g0), c1 = P.kappa * rcp_fast(d1 * g1);
  uint32_t cb = pack_h2(e0 ? c0 : 0.f, e1 ? c1 : 0.f);
  wg_wait<0>(); pin<24>(q);
  uint32_t old = 0;
  if (kSecond) {
    asm volatile("{\n.reg .pred p;\nsetp.eq.u32 p, %2, 0;\n@p atom.relaxed.cta.shared::cta.inc.u32 %0, [%1], 7;\n}"
                 : "+r"(old) : "r"(sb + kOffBar + 80 + ia * 4), "r"(lane) : "memory");
  }
  if (!have && LQ < 2) {
    if (kSecond && i + 1 < nw) mbar_wait(barN, parN);
    s_load(vn, bufn, fn);
  }
#pragma unroll
  for (int j = 0; j < 12; j++) { u[2 * j] = h2mul(q[2 * j], lo2(cb)); u[2 * j + 1] = h2mul(q[2 * j + 1], hi2(cb)); }
  gemm_w<2>(v, u, dQ + (kWMat >> 4), !wide);
  if (LQ == 2) {
    if (kSecond && i + 1 < nw) mbar_wait(barN, parN);
    s_load(vn, bufn, fn);
  }
  gemm_w<2>(q, vn, dQ, never);
  if (kSecond) {
    if (UNLIKELY(old == (RL ? 1 : 7))) {
      const uint32_t bar = sb + kOffBar + ia * 8;
      if (i + 4 < nw) {
        mbar_expect(bar, kXBytes);
        tma_load_win(buf, tm, bar, i + 5 == nw ? wlast : w + 4 * gridDim.x);
      } else if (i + 4 == nw) {
        mbar_arrive(bar);
      }
    }
    __syncwarp();
  }
  const bool plain = !(wide | f.light);
  wg_wait<1>(); pin<24>(v);
  if (LIKELY(plain)) s_store<0, true>(v, e0, ob + f.o0);
  wg_wait<0>(); pin<24>(q);
  gemm_s(s, q, bufn + fn.pl);
  if (LIKELY(plain)) s_store<1, true>(v, e1, ob + f.o1);
  else if (!wide) { s_store<0, false>(v, e0, ob + f.o0); __syncwarp(); }
  else if (wide) { s_store_wide<0, true>(v, e0, ob + f.o0, P); s_store_wide<1, true>(v, e1, ob + f.o1, P); }
  wg_wait<0>(); pin<14>(s);
}

__device__ __forceinline__ void loop_S(uint32_t sb, int nw, bool half, uint32_t wlast, int t0, int wp, int lane, const Params& P, bool scaled,
                                       const CUtensorMap* tm, uint8_t* __restrict__ out) {
  const SFrame f0 = s_frame(t0, wp, lane), f1 = s_frame(t0 ^ 2, wp, lane);
  uint32_t v0[24], v1[24], q[24], s[16];
  mbar_wait(sb + kOffBarW + 8, 0);
  mbar_wait(sb + kOffBar + 32, 0);
  s_load(v0, sb + kOffBuf, f0);
  gemm_w<0>(q, v0, mk_desc(sb + kOffAs, 1));
  wg_wait<0>(); pin<24>(q);
  gemm_s(s, q, sb + kOffBuf + f0.pl);
  wg_wait<0>(); pin<14>(s);
  uint32_t w = blockIdx.x;
  for (uint32_t i = 0; i < nw; i++, w += gridDim.x) {
    if (i + 1 == nw) w = wlast;
    const uint32_t wy = (w * 57457u) >> 22;
    uint8_t* ob = out + (size_t)((wy * (7 * kW - 7 * kNWX) + w * 7) * 192u);
    asm volatile("" : "+l"(ob));
    step_S<0>(sb, v0, v1, q, s, f0, f1, i, nw, w, wlast, ob, lane, P, scaled, tm);
    if (half && i + 1 == nw) break;
    step_S<1>(sb, v1, v0, q, s, f1, f0, i, nw, w, wlast, ob, lane, P, scaled, tm);
  }
}

__global__ void __launch_bounds__(LB, 1) swin_main(const __grid_constant__ CUtensorMap tm, uint8_t* __restrict__ out) {
  extern __shared__ __align__(1024) uint8_t smem[];
  const uint32_t sb = smem_u32(smem);
  const int tid = threadIdx.x;
  const int wg = __shfl_sync(0xffffffffu, tid >> 7, 0);
  const int wp = __shfl_sync(0xffffffffu, (tid >> 5) & 3, 0);
  const int lane = tid & 31;
  const int b = blockIdx.x, nb = gridDim.x;
  const int nfull = kNWIN / nb, nrem = kNWIN - nfull * nb;
  const bool share = 2 * nrem <= nb;
  const int nw = nfull + (b < (share ? 2 * nrem : nrem));
  const bool half = share && nw > nfull;
  const uint32_t wlast = half && b >= nrem ? b - nrem + nfull * nb : b + (nw - 1) * nb;
  const uint32_t tshift = half && b >= nrem ? 2 : 0;
  if (tid == 0) {
    if ((sb & 1023) || nw > 700 || nw < 5) __trap();
#pragma unroll
    for (int i = 0; i < 4; i++) {
      mbar_init(sb + kOffBar + i * 8, 1);
      mbar_init(sb + kOffBar + 32 + i * 8, 7);
      asm volatile("st.shared.b32 [%0], %1;" ::"r"(sb + kOffBar + 80 + i * 4), "r"(0) : "memory");
    }
    asm volatile("st.shared.v2.b32 [%0], {%1,%1};" ::"r"(sb + kOffFlag), "r"(0) : "memory");
    mbar_init(sb + kOffBarW, 1); mbar_init(sb + kOffBarW + 8, 1);
    asm volatile("fence.mbarrier_init.release.cluster;" ::: "memory");
    for (int i = 0; i < 2; i++) {
      mbar_expect(sb + kOffBar + i * 8, kXBytes);
      tma_load_win(sb + kOffBuf + i * kBufStride, &tm, sb + kOffBar + i * 8, b + i * nb);
    }
  }
  if (tid >= 128 && tid < 448) {
    asm volatile("st.shared.v4.b32 [%0], {%1,%1,%1,%1};" ::"r"(sb + kOffBuf + ((tid - 128) / 80) * kBufStride + kXBytes + ((tid - 128) % 80) * 16), "r"(0) : "memory");
    asm volatile("fence.proxy.async.shared::cta;" ::: "memory");
  }
  __syncthreads();
  asm volatile("griddepcontrol.wait;" ::: "memory");
  if (tid == 256) {
    asm volatile("fence.proxy.async.global;" ::: "memory");
#pragma unroll
    for (int i = 0; i < 2; i++) {
      const uint32_t o = i ? kOffAs : 0, n = i ? kWBytes - kOffAs : kOffAs, bar = sb + kOffBarW + 8 * i;
      mbar_expect(bar, n);
      asm volatile("cp.async.bulk.shared::cluster.global.mbarrier::complete_tx::bytes [%0], [%1], %2, [%3];"
                   ::"r"(sb + o), "l"(reinterpret_cast<const uint8_t*>(g_wimg) + o), "r"(n), "r"(bar) : "memory");
    }
    for (int i = 2; i < 4; i++) {
      mbar_expect(sb + kOffBar + i * 8, kXBytes);
      tma_load_win(sb + kOffBuf + i * kBufStride, &tm, sb + kOffBar + i * 8, b + i * nb);
    }
  }
  __syncwarp();
  Params P;
  {
    const float4 p0 = __ldcg(reinterpret_cast<const float4*>(&g_par));
    P.cS_t = p0.x; P.cS_s = p0.y; P.kt = p0.z; P.kappa = p0.w;
  }
  const bool scaled = __any_sync(0xffffffffu, P.cS_s != 1.f);
  const bool direct = __all_sync(0xffffffffu, (P.cS_t == 1.f) & (P.kt <= 256.f));
  const int widx = __popc(((ROLE >> wg) & 1 ? ROLE : ~ROLE) & ((1 << wg) - 1));
  if ((ROLE >> wg) & 1) {
    loop_T(sb, nw, widx, wp, lane, P, direct);
  } else {
    loop_S(sb, nw, half, wlast, widx + tshift, wp, lane, P, scaled, &tm, out);
  }
}

__device__ __forceinline__ int ch_pos(int ch) { return 32 * (ch >> 5) + 8 * ((ch >> 1) & 3) + 2 * ((ch >> 3) & 3) + (ch & 1); }
__device__ __forceinline__ float pow2_ceil(float v) {
  return __uint_as_float((__float_as_uint(v) + 0x7fffffu) & 0x7f800000u);
}

constexpr int kPrepSplit = 12;
constexpr int kPrepThreads = 384;
__global__ void __launch_bounds__(kPrepThreads) swin_prep(const __nv_bfloat16* __restrict__ wqkv_t, const __nv_bfloat16* __restrict__ wo_t,
                                                          const __nv_bfloat16* __restrict__ wqkv_s, const __nv_bfloat16* __restrict__ wo_s) {
  asm volatile("griddepcontrol.launch_dependents;");
  __shared__ __align__(16) uint32_t raw[2][96][52];
  __shared__ __align__(16) uint32_t mu[3][52];
  __shared__ float nrm[12], nrm2[6], csum[6][9];
  const int mat = blockIdx.x / kPrepSplit, blk = blockIdx.x % kPrepSplit;
  const int tid = threadIdx.x, lane = tid & 31, warp = tid >> 5, g = lane >> 2, c = lane & 3;
  const __nv_bfloat16* wqkv = mat < 2 ? wqkv_t : wqkv_s;
  const __nv_bfloat16* wo = mat < 2 ? wo_t : wo_s;
  const bool isA = (mat & 1) == 0;
  {
    uint4 v[3], u[3];
#pragma unroll
    for (int q = 0; q < 3; q++) {
      const int e = tid + q * kPrepThreads, i = e / 12, c8 = (e % 12) * 8;
      v[q] = __ldg(reinterpret_cast<const uint4*>(wqkv + i * 288 + (isA ? 0 : 192) + c8));
      u[q] = __ldg(reinterpret_cast<const uint4*>(isA ? wqkv + i * 288 + 96 + c8 : wo + i * 96 + c8));
    }
#pragma unroll
    for (int q = 0; q < 3; q++) {
      const int e = tid + q * kPrepThreads, i = e / 12, c4 = (e % 12) * 4;
      *reinterpret_cast<uint4*>(&raw[0][i][c4]) = v[q];
      *reinterpret_cast<uint4*>(&raw[1][i][c4]) = u[q];
    }
  }
  __syncthreads();
  {
    const int m = warp / 6, cp = (warp % 6) * 8 + g;
    float s0 = 0.f, s1 = 0.f, q0 = 0.f, q1 = 0.f;
#pragma unroll
    for (int i = 0; i < 24; i++) {
      const uint32_t w = raw[m][4 * i + c][cp];
      const float lo = __uint_as_float(w << 16), hi = __uint_as_float(w & 0xffff0000u);
      s0 += lo; s1 += hi; q0 = fmaf(lo, lo, q0); q1 = fmaf(hi, hi, q1);
    }
    s0 = quad_sum(s0) * (1.f / 96.f); s1 = quad_sum(s1) * (1.f / 96.f); q0 = quad_sum(q0); q1 = quad_sum(q1);
    if (mat == 1 && m == 1) {
      float r0 = 0.f, r1 = 0.f;
#pragma unroll
      for (int i = 0; i < 12; i++) {
        const uint32_t w0 = raw[1][2 * cp][4 * i + c], w1 = raw[1][2 * cp + 1][4 * i + c];
        r0 += __uint_as_float(w0 << 16) + __uint_as_float(w0 & 0xffff0000u);
        r1 += __uint_as_float(w1 << 16) + __uint_as_float(w1 & 0xffff0000u);
      }
      r0 = quad_sum(r0) * (1.f / 96.f); r1 = quad_sum(r1) * (1.f / 96.f);
      s0 = r0; s1 = r1;
    }
    if (m == 1 && c == 0) {
      const uint32_t hi = mat == 3 ? 0u : pack_bf2(s0, s1);
      mu[0][cp] = hi;
      mu[1][cp] = mat == 3 ? 0u : pack_bf2(s0 - __uint_as_float(hi << 16), s1 - __uint_as_float(hi & 0xffff0000u));
      mu[2][cp] = 0u;
    }
    if (m == 0 || isA) {
      q0 = fmaxf(fmaf(-96.f * s0, s0, q0), 0.f) + q0 * 1e-6f;
      q1 = fmaxf(fmaf(-96.f * s1, s1, q1), 0.f) + q1 * 1e-6f;
    }
    const bool usemax = m == 1 && mat == 3;
    float t = usemax ? fmaxf(q0, q1) : q0 + q1;
#pragma unroll
    for (int o = 4; o < 32; o <<= 1) { const float z = __shfl_xor_sync(0xffffffffu, t, o); t = usemax ? fmaxf(t, z) : t + z; }
    if (lane == 0) nrm[warp] = t;
  }
  __syncthreads();
  if (warp >= 6) return;
  float d[4] = {0.f, 0.f, 0.f, 0.f}, e[4] = {0.f, 0.f, 0.f, 0.f}, v0, v1;
  {
    const uint32_t arow = smem_u32(&raw[0][16 * warp + (lane & 15)][(lane >> 4) * 4]);
    const uint32_t brow = isA ? smem_u32(&raw[1][blk * 8 + (lane & 7)][(lane >> 3) * 4]) : smem_u32(&raw[1][lane][blk * 4]);
    const uint32_t mrow = smem_u32(&mu[min(lane & 7, 2)][(lane >> 3) * 4]);
#pragma unroll
    for (int k2 = 0; k2 < 3; k2++) {
      uint32_t b[4], m[4];
      if (isA) ldsm4(b, brow + k2 * 64);
      else asm volatile("ldmatrix.sync.aligned.m8n8.x4.trans.shared.b16 {%0,%1,%2,%3}, [%4];"
                        : "=r"(b[0]), "=r"(b[1]), "=r"(b[2]), "=r"(b[3]) : "r"(brow + k2 * (32 * 208)) : "memory");
      ldsm4(m, mrow + k2 * 64);
#pragma unroll
      for (int hf = 0; hf < 2; hf++) {
        uint32_t a[4];
        ldsm4(a, arow + (2 * k2 + hf) * 32);
        asm volatile("mma.sync.aligned.m16n8k16.row.col.f32.bf16.bf16.f32 {%0,%1,%2,%3},{%4,%5,%6,%7},{%8,%9},{%0,%1,%2,%3};"
                     : "+f"(d[0]), "+f"(d[1]), "+f"(d[2]), "+f"(d[3])
                     : "r"(a[0]), "r"(a[1]), "r"(a[2]), "r"(a[3]), "r"(b[2 * hf]), "r"(b[2 * hf + 1]));
        asm volatile("mma.sync.aligned.m16n8k16.row.col.f32.bf16.bf16.f32 {%0,%1,%2,%3},{%4,%5,%6,%7},{%8,%9},{%0,%1,%2,%3};"
                     : "+f"(e[0]), "+f"(e[1]), "+f"(e[2]), "+f"(e[3])
                     : "r"(a[0]), "r"(a[1]), "r"(a[2]), "r"(a[3]), "r"(m[2 * hf]), "r"(m[2 * hf + 1]));
      }
    }
    v0 = __shfl_sync(0xffffffffu, e[0] + e[1], lane & ~3); v1 = __shfl_sync(0xffffffffu, e[2] + e[3], lane & ~3);
    d[0] -= v0; d[1] -= v0; d[2] -= v1; d[3] -= v1;
    float t0 = d[0] + d[2], t1 = d[1] + d[3], t2 = v0 + v1;
#pragma unroll
    for (int o = 4; o < 32; o <<= 1) {
      t0 += __shfl_xor_sync(0xffffffffu, t0, o); t1 += __shfl_xor_sync(0xffffffffu, t1, o); t2 += __shfl_xor_sync(0xffffffffu, t2, o);
    }
    if (g == 0) { csum[warp][2 * c] = t0; csum[warp][2 * c + 1] = t1; csum[warp][8] = t2; }
  }
  const float nl = nrm[0] + nrm[1] + nrm[2] + nrm[3] + nrm[4] + nrm[5];
  const float nr = mat == 3 ? fmaxf(fmaxf(fmaxf(nrm[6], nrm[7]), fmaxf(nrm[8], nrm[9])), fmaxf(nrm[10], nrm[11]))
                            : nrm[6] + nrm[7] + nrm[8] + nrm[9] + nrm[10] + nrm[11];
  const float bound = __fsqrt_rn(nl) * __fsqrt_rn(nr) * 1.01f;
  const float f = isA ? 0.14724448f : 1.f;
  float sc = pow2_ceil(fmaxf(bound * (isA ? 0.14724448f / 160.f : mat == 1 ? 1.f / 16.f : 1.f / 64.f), 1e-30f));
  if (isA) sc = fminf(fmaxf(sc, 1.f), 32768.f);
  const float mul = f * __uint_as_float(0x7f000000u - __float_as_uint(sc));
  if (blk == 0 && tid == 0) (mat == 0 ? g_par.cS_t : mat == 1 ? g_par.kt : mat == 2 ? g_par.cS_s : g_par.kappa) = sc;
  asm volatile("bar.sync 1, 192;" ::: "memory");
  float mean[2];
#pragma unroll
  for (int b = 0; b < 2; b++)
    mean[b] = (csum[0][2 * c + b] + csum[1][2 * c + b] + csum[2][2 * c + b] + csum[3][2 * c + b] + csum[4][2 * c + b] + csum[5][2 * c + b]) *
              (1.f / 96.f);
  uint8_t* img = reinterpret_cast<uint8_t*>(g_wimg) + (mat == 0 ? 0 : mat == 1 ? kOffWt : mat == 2 ? kOffAs : kOffWs);
  const float vmean = (csum[0][8] + csum[1][8] + csum[2][8] + csum[3][8] + csum[4][8] + csum[5][8]) * (1.f / 96.f);
  float off = 0.f;
  if (mat == 2) {
    float q2 = 0.f;
#pragma unroll
    for (int q = 0; q < 4; q++) q2 = fmaf(d[q] - mean[q & 1], d[q] - mean[q & 1], q2);
#pragma unroll
    for (int o = 16; o; o >>= 1) q2 += __shfl_xor_sync(0xffffffffu, q2, o);
    if (lane == 0) nrm2[warp] = q2;
    asm volatile("bar.sync 1, 192;" ::: "memory");
    q2 = nrm2[0] + nrm2[1] + nrm2[2] + nrm2[3] + nrm2[4] + nrm2[5];
    off = 1.5f * pow2_ceil(fmaxf(__fsqrt_rn(q2 * (1.f / 768.f)) * mul * 3.f, 1e-4f));
  }
#pragma unroll
  for (int q = 0; q < 4; q++) {
    const int kp = ch_pos(16 * warp + g + 8 * (q >> 1)), np = ch_pos(blk * 8 + 2 * c + (q & 1));
    const uint32_t ko = (kp >> 5) * (mat == 0 ? kAtChunk : 6144) + (kp & 31) * 2;
    uint32_t a = ko + np * 64;
    a ^= ((a >> 7) & 3) << 4;
    float o = (d[q] - mean[q & 1]) * mul;
    o = mat == 2 ? o + off : __uint_as_float((__float_as_uint(o) + 0x8000u) & 0xffff0000u);
    *reinterpret_cast<__half*>(img + a) = __float2half_rn(o);
    if (mat == 1 && blk == 0) {
      a = (kp >> 5) * kAtChunk + (kp & 31) * 2 + (96 + 2 * c + (q & 1)) * 64;
      a ^= ((a >> 7) & 3) << 4;
      *reinterpret_cast<__half*>(reinterpret_cast<uint8_t*>(g_wimg) + a) = __float2half_rn((q & 1) ? ((q >> 1 ? v1 : v0) - vmean) * mul : 1.f / 96.f);
    }
  }
}

typedef CUresult (*EncodeFn)(CUtensorMap*, CUtensorMapDataType, cuuint32_t, void*, const cuuint64_t*, const cuuint64_t*,
                             const cuuint32_t*, const cuuint32_t*, CUtensorMapInterleave, CUtensorMapSwizzle,
                             CUtensorMapL2promotion, CUtensorMapFloatOOBfill);

}

extern "C" void kernel_launch(void* const* d_in, const int* in_sizes, int n_in, void* d_out, int out_size) {
  (void)in_sizes; (void)n_in; (void)out_size;
  static EncodeFn enc = nullptr;
  static int nsm = 0;
  if (!enc) {
    void* fn = nullptr;
    cudaDriverEntryPointQueryResult qr;
    cudaGetDriverEntryPoint("cuTensorMapEncodeTiled", &fn, cudaEnableDefault, &qr);
    enc = reinterpret_cast<EncodeFn>(fn);
    int dev = 0;
    cudaGetDevice(&dev);
    cudaDeviceGetAttribute(&nsm, cudaDevAttrMultiProcessorCount, dev);
    cudaFuncSetAttribute(swin_main, cudaFuncAttributeMaxDynamicSharedMemorySize, kSmemBytes);
  }
  CUtensorMap tm;
  const cuuint64_t dims[5] = {32, kW, kH, kT, 3};
  const cuuint64_t strides[4] = {192, 192ull * kW, 192ull * kW * kH, 64};
  const cuuint32_t box[5] = {32, 7, 7, 4, 3};
  const cuuint32_t es[5] = {1, 1, 1, 1, 1};
  enc(&tm, CU_TENSOR_MAP_DATA_TYPE_BFLOAT16, 5, d_in[0], dims, strides, box, es, CU_TENSOR_MAP_INTERLEAVE_NONE,
      CU_TENSOR_MAP_SWIZZLE_64B, CU_TENSOR_MAP_L2_PROMOTION_L2_128B, CU_TENSOR_MAP_FLOAT_OOB_FILL_NONE);

  cudaStream_t st = cudaStreamPerThread;
  swin_prep<<<4 * kPrepSplit, kPrepThreads, 0, st>>>(
      static_cast<const __nv_bfloat16*>(d_in[1]), static_cast<const __nv_bfloat16*>(d_in[2]),
      static_cast<const __nv_bfloat16*>(d_in[3]), static_cast<const __nv_bfloat16*>(d_in[4]));

  cudaLaunchConfig_t cfg = {};
  cfg.gridDim = dim3(nsm);
  cfg.blockDim = dim3(kNWG * 128);
  cfg.dynamicSmemBytes = kSmemBytes;
  cfg.stream = st;
  cudaLaunchAttribute at[1];
  at[0].id = cudaLaunchAttributeProgrammaticStreamSerialization;
  at[0].val.programmaticStreamSerializationAllowed = 1;
  cfg.attrs = at;
  cfg.numAttrs = 1;
  cudaLaunchKernelEx(&cfg, swin_main, tm, static_cast<uint8_t*>(d_out));
}
```

```cpp
#include <cuda_runtime.h>
#include <cuda.h>
#include <cuda_bf16.h>
#include <cuda_fp16.h>
#include <stdint.h>

#define LB 512
#define SF 17
#define TIE 0
#define SG 1
#define IL 1
#define FP 0
#define ROLE 3
#define RF 1
#define CK0 0
#define LIKELY(x) __builtin_expect(!!(x), 1)
#define UNLIKELY(x) __builtin_expect(!!(x), 0)
#define CV 1
#define C1 2
#define C2 2
#define WS 1
#define TL 1
#define PAD 0
#define SPL 1
#define SPN 64
#define SPO 1
namespace {

constexpr int kH = 511, kW = 511, kT = 4;
constexpr int kNWX = 73, kNWIN = 73 * 73;
constexpr int kChunk = 3136;
constexpr int kXBytes = 3 * kChunk;
constexpr int kFrame = 9728;
constexpr int kBufStride = 4 * kFrame;
constexpr int kWMat = 18432;
constexpr int kAtChunk = 104 * 64;
constexpr int kOffWt = 3 * kAtChunk;
constexpr int kOffAs = kOffWt + kWMat, kOffWs = kOffAs + kWMat;
constexpr int kWBytes = kOffWs + kWMat;
constexpr int kOffBuf = kWBytes;
constexpr int kOffBar = kOffBuf + 4 * kBufStride + 640;
constexpr int kOffFlag = kOffBar + 64;
constexpr int kOffBarW = kOffBar + 80;
constexpr int kSmemBytes = kOffBar + 96;
constexpr int kNWG = 4;

struct Params {
  float cS_t, cS_s;
  float kt;
  float kappa;
  float sgmin;
};

__device__ uint4 g_wimg[kWBytes / 16];
__device__ __align__(16) Params g_par;

__device__ __forceinline__ uint32_t smem_u32(const void* p) { return (uint32_t)__cvta_generic_to_shared(p); }
__device__ __forceinline__ void mbar_init(uint32_t a, int c) { asm volatile("mbarrier.init.shared::cta.b64 [%0], %1;" ::"r"(a), "r"(c)); }
__device__ __forceinline__ void mbar_expect(uint32_t a, int bytes) {
  asm volatile("mbarrier.arrive.expect_tx.shared::cta.b64 _, [%0], %1;" ::"r"(a), "r"(bytes) : "memory");
}
__device__ __forceinline__ void mbar_arrive(uint32_t a) {
  asm volatile("mbarrier.arrive.shared::cta.b64 _, [%0];" ::"r"(a) : "memory");
}
__device__ __forceinline__ void mbar_wait(uint32_t a, uint32_t par) {
  asm volatile(
      "{\n.reg .pred p;\n.reg .u32 n;\n"
      "mbarrier.try_wait.parity.shared::cta.b64 p, [%0], %1;\n"
      "@p bra.uni WDONE;\n"
      "mov.u32 n, 0;\n"
      "WLOOP:\n"
      "mbarrier.try_wait.parity.shared::cta.b64 p, [%0], %1;\n"
      "@p bra.uni WDONE;\n"
      "add.u32 n, n, 1;\n"
      "setp.lt.u32 p, n, 0x1000000;\n"
      "@p bra.uni WLOOP;\n"
      "trap;\n"
      "WDONE:\n}" ::"r"(a), "r"(par) : "memory");
}
__device__ __forceinline__ void tma_load(uint32_t dst, const CUtensorMap* m, uint32_t bar, uint32_t w, uint32_t t) {
  const uint32_t wy = (w * 57457u) >> 22, wx = w - wy * kNWX;
  mbar_expect(bar, kXBytes);
  asm volatile(
      "cp.async.bulk.tensor.5d.shared::cluster.global.mbarrier::complete_tx::bytes [%0], [%1, {%3,%4,%5,%6,%3}], [%2];" ::"r"(dst),
      "l"(m), "r"(bar), "r"(0), "r"(wx * 7), "r"(wy * 7), "r"(t)
      : "memory");
}
__device__ __forceinline__ void wg_fence() { asm volatile("wgmma.fence.sync.aligned;" ::: "memory"); }
__device__ __forceinline__ void wg_commit() { asm volatile("wgmma.commit_group.sync.aligned;" ::: "memory"); }
template <int N>
__device__ __forceinline__ void wg_wait() { asm volatile("wgmma.wait_group.sync.aligned %0;" ::"n"(N) : "memory"); }
template <int N>
__device__ __forceinline__ void pin(uint32_t* d) {
#pragma unroll
  for (int i = 0; i < N; i++) asm volatile("" : "+r"(d[i])::"memory");
}
__device__ __forceinline__ void sched_fence(uint32_t a, uint32_t b, uint32_t c) {
  asm volatile("{\n.reg .pred p;\n.reg .b32 t;\nsetp.ne.u32 p, %0, 0x7fffffff;\n@p bra.uni SFD;\n"
               "add.u32 t, %1, %2;\nadd.u32 t, t, %3;\nnanosleep.u32 t;\nSFD:\n}" ::"r"(gridDim.x), "r"(a), "r"(b), "r"(c) : "memory");
}
__device__ __forceinline__ uint64_t mk_desc(uint32_t addr, uint32_t lbo16) {
  return ((uint64_t)0x80000020u << 32) | ((addr >> 4) & 0x3fff) | (lbo16 << 16);
}

#define R4(d, i) "+r"(d[i]), "+r"(d[i + 1]), "+r"(d[i + 2]), "+r"(d[i + 3])
#define O4(d, i) "=r"(d[i]), "=r"(d[i + 1]), "=r"(d[i + 2]), "=r"(d[i + 3])
#define D24 "{%0,%1,%2,%3,%4,%5,%6,%7,%8,%9,%10,%11,%12,%13,%14,%15,%16,%17,%18,%19,%20,%21,%22,%23},"
#define D14 "{%0,%1,%2,%3,%4,%5,%6,%7,%8,%9,%10,%11,%12,%13},"

template <int SC, int TB>
__device__ __forceinline__ void wg96h(uint32_t (&d)[24], const uint32_t* a, uint64_t db, uint32_t acc = 0) {
  if (SC == 2)
    asm volatile("{\n.reg .pred p;\nsetp.ne.u32 p, %30, 0;\n"
                 "wgmma.mma_async.sync.aligned.m64n96k16.f16.f16.f16 " D24 "{%24,%25,%26,%27}, %28, p, 1, 1, %29;\n}"
                 : R4(d, 0), R4(d, 4), R4(d, 8), R4(d, 12), R4(d, 16), R4(d, 20)
                 : "r"(a[0]), "r"(a[1]), "r"(a[2]), "r"(a[3]), "l"(db), "n"(TB), "r"(acc));
  else if (SC)
    asm volatile("wgmma.mma_async.sync.aligned.m64n96k16.f16.f16.f16 " D24 "{%24,%25,%26,%27}, %28, 1, 1, 1, %29;"
                 : R4(d, 0), R4(d, 4), R4(d, 8), R4(d, 12), R4(d, 16), R4(d, 20)
                 : "r"(a[0]), "r"(a[1]), "r"(a[2]), "r"(a[3]), "l"(db), "n"(TB));
  else
    asm volatile("wgmma.mma_async.sync.aligned.m64n96k16.f16.f16.f16 " D24 "{%24,%25,%26,%27}, %28, 0, 1, 1, %29;"
                 : O4(d, 0), O4(d, 4), O4(d, 8), O4(d, 12), O4(d, 16), O4(d, 20)
                 : "r"(a[0]), "r"(a[1]), "r"(a[2]), "r"(a[3]), "l"(db), "n"(TB));
}
template <int SC>
__device__ __forceinline__ void wg104h(uint32_t (&d)[26], const uint32_t* a, uint64_t db) {
  if (SC)
    asm volatile("wgmma.mma_async.sync.aligned.m64n104k16.f16.f16.f16 "
                 "{%0,%1,%2,%3,%4,%5,%6,%7,%8,%9,%10,%11,%12,%13,%14,%15,%16,%17,%18,%19,%20,%21,%22,%23,%24,%25},"
                 "{%26,%27,%28,%29}, %30, 1, 1, 1, 0;"
                 : R4(d, 0), R4(d, 4), R4(d, 8), R4(d, 12), R4(d, 16), R4(d, 20), "+r"(d[24]), "+r"(d[25])
                 : "r"(a[0]), "r"(a[1]), "r"(a[2]), "r"(a[3]), "l"(db));
  else
    asm volatile("wgmma.mma_async.sync.aligned.m64n104k16.f16.f16.f16 "
                 "{%0,%1,%2,%3,%4,%5,%6,%7,%8,%9,%10,%11,%12,%13,%14,%15,%16,%17,%18,%19,%20,%21,%22,%23,%24,%25},"
                 "{%26,%27,%28,%29}, %30, 0, 1, 1, 0;"
                 : O4(d, 0), O4(d, 4), O4(d, 8), O4(d, 12), O4(d, 16), O4(d, 20), "=r"(d[24]), "=r"(d[25])
                 : "r"(a[0]), "r"(a[1]), "r"(a[2]), "r"(a[3]), "l"(db));
}
template <int SC>
__device__ __forceinline__ void wg56h(uint32_t* d, const uint32_t* a, uint64_t db) {
  if (SC)
    asm volatile("wgmma.mma_async.sync.aligned.m64n56k16.f16.f16.f16 " D14 "{%14,%15,%16,%17}, %18, 1, 1, 1, 0;"
                 : R4(d, 0), R4(d, 4), R4(d, 8), "+r"(d[12]), "+r"(d[13])
                 : "r"(a[0]), "r"(a[1]), "r"(a[2]), "r"(a[3]), "l"(db));
  else
    asm volatile("wgmma.mma_async.sync.aligned.m64n56k16.f16.f16.f16 " D14 "{%14,%15,%16,%17}, %18, 0, 1, 1, 0;"
                 : O4(d, 0), O4(d, 4), O4(d, 8), "=r"(d[12]), "=r"(d[13])
                 : "r"(a[0]), "r"(a[1]), "r"(a[2]), "r"(a[3]), "l"(db));
}
template <int SC>
__device__ __forceinline__ void gemm_w(uint32_t (&d)[24], const uint32_t* a, uint64_t dw, uint32_t acc = 0) {
  wg_fence();
  wg96h<SC, 0>(d, a, dw, acc); wg96h<1, 0>(d, a + 4, dw + 2);
  wg96h<1, 0>(d, a + 8, dw + 384); wg96h<1, 0>(d, a + 12, dw + 386);
  wg96h<1, 0>(d, a + 16, dw + 768); wg96h<1, 0>(d, a + 20, dw + 770);
  wg_commit();
}
__device__ __forceinline__ void lds128(uint32_t* r, uint32_t a) {
  asm volatile("ld.shared.v4.b32 {%0,%1,%2,%3}, [%4];" : "=r"(r[0]), "=r"(r[1]), "=r"(r[2]), "=r"(r[3]) : "r"(a) : "memory");
}
__device__ __forceinline__ uint32_t lds32(uint32_t a) {
  uint32_t r; asm volatile("ld.volatile.shared.b32 %0, [%1];" : "=r"(r) : "r"(a) : "memory"); return r;
}
__device__ __forceinline__ void sts32(uint32_t a, uint32_t v) { asm volatile("st.volatile.shared.b32 [%0], %1;" ::"r"(a), "r"(v) : "memory"); }
__device__ __forceinline__ void ldsm4(uint32_t* r, uint32_t a) {
  asm volatile("ldmatrix.sync.aligned.m8n8.x4.shared.b16 {%0,%1,%2,%3}, [%4];"
               : "=r"(r[0]), "=r"(r[1]), "=r"(r[2]), "=r"(r[3]) : "r"(a) : "memory");
}
__device__ __forceinline__ void stsm4(uint32_t a, const uint32_t* r) {
  asm volatile("stmatrix.sync.aligned.m8n8.x4.shared.b16 [%0], {%1,%2,%3,%4};" ::"r"(a), "r"(r[0]), "r"(r[1]), "r"(r[2]), "r"(r[3])
               : "memory");
}
__device__ __forceinline__ uint32_t pack_h2(float lo, float hi) {
  uint32_t r; asm("cvt.rn.f16x2.f32 %0, %1, %2;" : "=r"(r) : "f"(hi), "f"(lo)); return r;
}
__device__ __forceinline__ uint32_t pack_h2_sat(float lo, float hi) {
  uint32_t r; asm("cvt.rn.satfinite.f16x2.f32 %0, %1, %2;" : "=r"(r) : "f"(hi), "f"(lo)); return r;
}
__device__ __forceinline__ uint32_t pack_bf2(float lo, float hi) {
  uint32_t r; asm("cvt.rn.bf16x2.f32 %0, %1, %2;" : "=r"(r) : "f"(hi), "f"(lo)); return r;
}
__device__ __forceinline__ __half2 as_h2(uint32_t v) { return *reinterpret_cast<__half2*>(&v); }
__device__ __forceinline__ uint32_t as_u(__half2 v) { return *reinterpret_cast<uint32_t*>(&v); }
__device__ __forceinline__ float2 unpack_h2(uint32_t v) { return __half22float2(as_h2(v)); }
__device__ __forceinline__ uint32_t h2ex2(uint32_t v) { uint32_t r; asm("ex2.approx.f16x2 %0, %1;" : "=r"(r) : "r"(v)); return r; }
__device__ __forceinline__ uint32_t h2max(uint32_t a, uint32_t b) { return as_u(__hmax2(as_h2(a), as_h2(b))); }
__device__ __forceinline__ uint32_t h2add(uint32_t a, uint32_t b) { return as_u(__hadd2(as_h2(a), as_h2(b))); }
__device__ __forceinline__ uint32_t h2sub(uint32_t a, uint32_t b) { return as_u(__hsub2(as_h2(a), as_h2(b))); }
__device__ __forceinline__ uint32_t h2mul(uint32_t a, uint32_t b) { return as_u(__hmul2(as_h2(a), as_h2(b))); }
__device__ __forceinline__ uint32_t h2fma(uint32_t a, uint32_t b, uint32_t c) { return as_u(__hfma2(as_h2(a), as_h2(b), as_h2(c))); }
__device__ __forceinline__ uint32_t lo2(uint32_t v) { return as_u(__low2half2(as_h2(v))); }
__device__ __forceinline__ uint32_t hi2(uint32_t v) { return as_u(__high2half2(as_h2(v))); }
__device__ __forceinline__ uint32_t fold_add(uint32_t a, uint32_t b) { return h2add(__byte_perm(a, b, 0x5410), __byte_perm(a, b, 0x7632)); }
__device__ __forceinline__ uint32_t bitsel(uint32_t a, uint32_t m, uint32_t c) {
  uint32_t r; asm("lop3.b32 %0, %1, %2, %3, 0xe2;" : "=r"(r) : "r"(a), "r"(m), "r"(c)); return r;
}
__device__ __forceinline__ float rcp_fast(float v) { float r; asm("rcp.approx.ftz.f32 %0, %1;" : "=f"(r) : "f"(v)); return r; }
__device__ __forceinline__ float rsq_fast(float v) { float r; asm("rsqrt.approx.ftz.f32 %0, %1;" : "=f"(r) : "f"(v)); return r; }
__device__ __forceinline__ float quad_sum(float v) {
  v += __shfl_xor_sync(0xffffffffu, v, 1);
  return v + __shfl_xor_sync(0xffffffffu, v, 2);
}
__device__ __forceinline__ uint32_t quad_h2add(uint32_t v) {
  v = h2add(v, __shfl_xor_sync(0xffffffffu, v, 1));
  return h2add(v, __shfl_xor_sync(0xffffffffu, v, 2));
}
__device__ __forceinline__ uint32_t score_scale(const float* p) { const float v = __ldcg(p); return pack_h2(v, v); }

constexpr float kEps96 = 1e-5f * 96.f * 96.f;
__device__ __forceinline__ float2 stat_f32(uint32_t e) {
  const float2 h = unpack_h2(e);
  return make_float2((e & 0x8000u) ? __uint_as_float((e << 16) & 0x7fff0000u) : h.x, (e & 0x8000u) ? __uint_as_float(e & 0xffff0000u) : h.y);
}

__device__ __forceinline__ uint32_t swz(uint32_t a) { return a ^ ((a >> 3) & 0x30); }
__device__ __forceinline__ uint32_t prmt(uint32_t a, uint32_t b, uint32_t s) {
  uint32_t r; asm("prmt.b32 %0, %1, %2, %3;" : "=r"(r) : "r"(a), "r"(b), "r"(s)); return r;
}
__device__ __forceinline__ void tie48(uint32_t* a, uint32_t* b, uint64_t d, uint32_t u = 0, uint32_t v = 0) {
  asm volatile("{\n.reg .pred p;\n.reg .b32 t;\nsetp.ne.u32 p, %48, 0x7fffffff;\n@p bra.uni TIED;\n"
               "wgmma.fence.sync.aligned;\n"
               "wgmma.mma_async.sync.aligned.m64n192k16.f16.f16.f16 {%0,%1,%2,%3,%4,%5,%6,%7,%8,%9,%10,%11,%12,%13,%14,%15,%16,%17,%18,%19,%20,%21,%22,%23,%24,%25,%26,%27,%28,%29,%30,%31,%32,%33,%34,%35,%36,%37,%38,%39,%40,%41,%42,%43,%44,%45,%46,%47}, %49, %49, 1, 1, 1, 0, 0;\n"
               "wgmma.commit_group.sync.aligned;\nwgmma.wait_group.sync.aligned 0;\nTIED:\n}"
               : R4(a, 0), R4(a, 4), R4(a, 8), R4(a, 12), R4(a, 16), R4(a, 20), R4(b, 0), R4(b, 4), R4(b, 8), R4(b, 12), R4(b, 16), R4(b, 20)
               : "r"(gridDim.x), "l"(d), "r"(u), "r"(v) : "memory");
}
struct A3 { uint32_t a[3]; };
__device__ __forceinline__ A3 swz3(uint32_t a) { return A3{{swz(a), swz(a + kChunk), swz(a + 2 * kChunk)}}; }
__device__ __forceinline__ void load_row(uint32_t* x, const A3& a, int t) {
  lds128(x, a.a[0] + t * kFrame); lds128(x + 4, a.a[1] + t * kFrame); lds128(x + 8, a.a[2] + t * kFrame);
}
__device__ __forceinline__ void row_to_h2(uint32_t* y, const uint32_t* x) {
#pragma unroll
  for (int j = 0; j < 12; j += 2) {
    y[2 * j] = pack_h2(__uint_as_float(x[j] << 16), __uint_as_float(x[j + 1] << 16));
    uint32_t r;
    asm("cvt.rz.f16x2.f32 %0, %1, %2;" : "=r"(r) : "f"(__uint_as_float(x[j + 1])), "f"(__uint_as_float(x[j])));
    y[2 * j + 2] = r & 0xfff8fff8u;
  }
}
__device__ __forceinline__ void gemm_at(uint32_t (&q)[26], const uint32_t* z, uint64_t da) {
  wg_fence();
  wg104h<0>(q, z, da); wg104h<1>(q, z + 4, da + 2);
  wg104h<1>(q, z + 8, da + 416); wg104h<1>(q, z + 12, da + 418);
  wg104h<1>(q, z + 16, da + 832); wg104h<1>(q, z + 20, da + 834);
  wg_commit();
}
template <int SC>
__device__ __forceinline__ void wg64h(uint32_t* d, const uint32_t* a, uint64_t db) {
  if (SC)
    asm volatile("wgmma.mma_async.sync.aligned.m64n64k16.f16.f16.f16 {%0,%1,%2,%3,%4,%5,%6,%7,%8,%9,%10,%11,%12,%13,%14,%15}, {%16,%17,%18,%19}, %20, 1, 1, 1, 0;"
                 : "+r"(d[0]), "+r"(d[1]), "+r"(d[2]), "+r"(d[3]), "+r"(d[4]), "+r"(d[5]), "+r"(d[6]), "+r"(d[7]), "+r"(d[8]), "+r"(d[9]), "+r"(d[10]), "+r"(d[11]), "+r"(d[12]), "+r"(d[13]), "+r"(d[14]), "+r"(d[15])
                 : "r"(a[0]), "r"(a[1]), "r"(a[2]), "r"(a[3]), "l"(db));
  else
    asm volatile("wgmma.mma_async.sync.aligned.m64n64k16.f16.f16.f16 {%0,%1,%2,%3,%4,%5,%6,%7,%8,%9,%10,%11,%12,%13,%14,%15}, {%16,%17,%18,%19}, %20, 0, 1, 1, 0;"
                 : "=r"(d[0]), "=r"(d[1]), "=r"(d[2]), "=r"(d[3]), "=r"(d[4]), "=r"(d[5]), "=r"(d[6]), "=r"(d[7]), "=r"(d[8]), "=r"(d[9]), "=r"(d[10]), "=r"(d[11]), "=r"(d[12]), "=r"(d[13]), "=r"(d[14]), "=r"(d[15])
                 : "r"(a[0]), "r"(a[1]), "r"(a[2]), "r"(a[3]), "l"(db));
}
template <int SC>
__device__ __forceinline__ void wg40h(uint32_t* d, const uint32_t* a, uint64_t db) {
  if (SC)
    asm volatile("wgmma.mma_async.sync.aligned.m64n40k16.f16.f16.f16 {%0,%1,%2,%3,%4,%5,%6,%7,%8,%9}, {%10,%11,%12,%13}, %14, 1, 1, 1, 0;"
                 : "+r"(d[0]), "+r"(d[1]), "+r"(d[2]), "+r"(d[3]), "+r"(d[4]), "+r"(d[5]), "+r"(d[6]), "+r"(d[7]), "+r"(d[8]), "+r"(d[9])
                 : "r"(a[0]), "r"(a[1]), "r"(a[2]), "r"(a[3]), "l"(db));
  else
    asm volatile("wgmma.mma_async.sync.aligned.m64n40k16.f16.f16.f16 {%0,%1,%2,%3,%4,%5,%6,%7,%8,%9}, {%10,%11,%12,%13}, %14, 0, 1, 1, 0;"
                 : "=r"(d[0]), "=r"(d[1]), "=r"(d[2]), "=r"(d[3]), "=r"(d[4]), "=r"(d[5]), "=r"(d[6]), "=r"(d[7]), "=r"(d[8]), "=r"(d[9])
                 : "r"(a[0]), "r"(a[1]), "r"(a[2]), "r"(a[3]), "l"(db));
}
template <int SC>
__device__ __forceinline__ void wg80h(uint32_t* d, const uint32_t* a, uint64_t db) {
  if (SC)
    asm volatile("wgmma.mma_async.sync.aligned.m64n80k16.f16.f16.f16 {%0,%1,%2,%3,%4,%5,%6,%7,%8,%9,%10,%11,%12,%13,%14,%15,%16,%17,%18,%19}, {%20,%21,%22,%23}, %24, 1, 1, 1, 0;"
                 : "+r"(d[0]), "+r"(d[1]), "+r"(d[2]), "+r"(d[3]), "+r"(d[4]), "+r"(d[5]), "+r"(d[6]), "+r"(d[7]), "+r"(d[8]), "+r"(d[9]), "+r"(d[10]), "+r"(d[11]), "+r"(d[12]), "+r"(d[13]), "+r"(d[14]), "+r"(d[15]), "+r"(d[16]), "+r"(d[17]), "+r"(d[18]), "+r"(d[19])
                 : "r"(a[0]), "r"(a[1]), "r"(a[2]), "r"(a[3]), "l"(db));
  else
    asm volatile("wgmma.mma_async.sync.aligned.m64n80k16.f16.f16.f16 {%0,%1,%2,%3,%4,%5,%6,%7,%8,%9,%10,%11,%12,%13,%14,%15,%16,%17,%18,%19}, {%20,%21,%22,%23}, %24, 0, 1, 1, 0;"
                 : "=r"(d[0]), "=r"(d[1]), "=r"(d[2]), "=r"(d[3]), "=r"(d[4]), "=r"(d[5]), "=r"(d[6]), "=r"(d[7]), "=r"(d[8]), "=r"(d[9]), "=r"(d[10]), "=r"(d[11]), "=r"(d[12]), "=r"(d[13]), "=r"(d[14]), "=r"(d[15]), "=r"(d[16]), "=r"(d[17]), "=r"(d[18]), "=r"(d[19])
                 : "r"(a[0]), "r"(a[1]), "r"(a[2]), "r"(a[3]), "l"(db));
}
template <int SC>
__device__ __forceinline__ void wg24h(uint32_t* d, const uint32_t* a, uint64_t db) {
  if (SC)
    asm volatile("wgmma.mma_async.sync.aligned.m64n24k16.f16.f16.f16 {%0,%1,%2,%3,%4,%5}, {%6,%7,%8,%9}, %10, 1, 1, 1, 0;"
                 : "+r"(d[0]), "+r"(d[1]), "+r"(d[2]), "+r"(d[3]), "+r"(d[4]), "+r"(d[5])
                 : "r"(a[0]), "r"(a[1]), "r"(a[2]), "r"(a[3]), "l"(db));
  else
    asm volatile("wgmma.mma_async.sync.aligned.m64n24k16.f16.f16.f16 {%0,%1,%2,%3,%4,%5}, {%6,%7,%8,%9}, %10, 0, 1, 1, 0;"
                 : "=r"(d[0]), "=r"(d[1]), "=r"(d[2]), "=r"(d[3]), "=r"(d[4]), "=r"(d[5])
                 : "r"(a[0]), "r"(a[1]), "r"(a[2]), "r"(a[3]), "l"(db));
}
__device__ __forceinline__ void gemm_at2(uint32_t (&q)[26], const uint32_t* z, uint64_t da) {
  wg_fence();
#define WA wg64h
#define WB wg40h
  constexpr int o = SPN / 4, e = SPN * 4;
  WA<0>(q, z, da); WB<0>(q + o, z, da + e); WA<1>(q, z + 4, da + 2); WB<1>(q + o, z + 4, da + e + 2);
  WA<1>(q, z + 8, da + 416); WB<1>(q + o, z + 8, da + e + 416); WA<1>(q, z + 12, da + 418); WB<1>(q + o, z + 12, da + e + 418);
  WA<1>(q, z + 16, da + 832); WB<1>(q + o, z + 16, da + e + 832); WA<1>(q, z + 20, da + 834); WB<1>(q + o, z + 20, da + e + 834);
  wg_commit();
}
template <int kChains = 2>
__device__ __forceinline__ uint32_t sumsq(const uint32_t* z) {
  if (kChains == 1) {
    uint32_t a = h2mul(z[0], z[0]), b = h2mul(z[1], z[1]);
#pragma unroll
    for (int j = 1; j < 12; j++) { a = h2fma(z[2 * j], z[2 * j], a); b = h2fma(z[2 * j + 1], z[2 * j + 1], b); }
    return fold_add(a, b);
  }
  uint32_t q0[2], q1[2];
#pragma unroll
  for (int j = 0; j < 12; j++) {
    const uint32_t u = z[2 * j], v = z[2 * j + 1];
    q0[j & 1] = j < 2 ? h2mul(u, u) : h2fma(u, u, q0[j & 1]); q1[j & 1] = j < 2 ? h2mul(v, v) : h2fma(v, v, q1[j & 1]);
  }
  return fold_add(h2add(q0[0], q0[1]), h2add(q1[0], q1[1]));
}
__device__ __forceinline__ void scores_e(uint32_t* e, const uint32_t* q, const uint32_t* z) {
  uint32_t d[4];
#pragma unroll
  for (int j = 0; j < 12; j++) {
#pragma unroll
    for (int k = 0; k < 4; k++) d[k] = j ? h2fma(q[2 * j + (k >> 1)], z[2 * j + (k & 1)], d[k]) : h2mul(q[k >> 1], z[k & 1]);
  }
  e[0] = fold_add(d[0], d[2]); e[1] = fold_add(d[1], d[3]);
}
__device__ __forceinline__ uint32_t scores_r(const uint32_t* e, uint32_t selK) {
  return h2add(prmt(e[0], e[1], selK), __shfl_xor_sync(0xffffffffu, prmt(e[0], e[1], selK ^ 0x2222u), 1));
}
__device__ __forceinline__ uint32_t scores(const uint32_t* q, const uint32_t* z, uint32_t selK) {
  uint32_t e[2];
  scores_e(e, q, z);
  return scores_r(e, selK);
}
__device__ __forceinline__ float2 rstd(float2 d) { return make_float2(rsq_fast(fmaf(d.x, 1.f / 96.f, 1e-5f)), rsq_fast(fmaf(d.y, 1.f / 96.f, 1e-5f))); }
__device__ __forceinline__ void ln1_f32(uint32_t* z, const A3& la, int t, float* ie, float* m) {
  float acc[48];
  uint32_t x0[12], x1[12];
  load_row(x0, la, t); load_row(x1, la, t + 1);
#pragma unroll
  for (int j = 0; j < 12; j++) {
    acc[4 * j] = __uint_as_float(x0[j] << 16); acc[4 * j + 1] = __uint_as_float(x0[j] & 0xffff0000u);
    acc[4 * j + 2] = __uint_as_float(x1[j] << 16); acc[4 * j + 3] = __uint_as_float(x1[j] & 0xffff0000u);
  }
  float s[4], q[4];
#pragma unroll
  for (int e = 0; e < 4; e++) { s[e] = acc[e]; q[e] = acc[e] * acc[e]; }
#pragma unroll
  for (int j = 4; j < 48; j++) { s[j & 3] += acc[j]; q[j & 3] = fmaf(acc[j], acc[j], q[j & 3]); }
  const float s0 = quad_sum(s[0] + s[1]), s1 = quad_sum(s[2] + s[3]), q0 = quad_sum(q[0] + q[1]), q1 = quad_sum(q[2] + q[3]);
  const float u0 = rsq_fast(fmaxf(fmaf(-s0, s0, fmaf(q0, 96.f, kEps96)), kEps96));
  const float u1 = rsq_fast(fmaxf(fmaf(-s1, s1, fmaf(q1, 96.f, kEps96)), kEps96));
  const float n0 = -s0 * u0, n1 = -s1 * u1;
  ie[0] = 96.f * u0; ie[1] = 96.f * u1;
  m[0] = s0 * (1.f / 96.f); m[1] = s1 * (1.f / 96.f);
#pragma unroll
  for (int j = 0; j < 12; j++) {
    const int e = 4 * (j & ~1) + (j & 1);
    z[2 * j] = pack_h2(fmaf(acc[e], ie[0], n0), fmaf(acc[e + 4], ie[0], n0));
    z[2 * j + 1] = pack_h2(fmaf(acc[e + 2], ie[1], n1), fmaf(acc[e + 6], ie[1], n1));
  }
}
__device__ __forceinline__ float2 sumsq_f32(const uint32_t* z) {
  float2 qq = make_float2(0.f, 0.f);
#pragma unroll
  for (int j = 0; j < 12; j++) {
    const float2 u = unpack_h2(z[2 * j]), v = unpack_h2(z[2 * j + 1]);
    qq.x = fmaf(u.x, u.x, fmaf(u.y, u.y, qq.x)); qq.y = fmaf(v.x, v.x, fmaf(v.y, v.y, qq.y));
  }
  return make_float2(quad_sum(qq.x), quad_sum(qq.y));
}
__device__ __forceinline__ float2 var96_f32(const uint32_t* z, uint32_t my) {
  const float2 q = sumsq_f32(z), m = unpack_h2(my);
  return make_float2(fmaf(-96.f * m.x, m.x, q.x), fmaf(-96.f * m.y, m.y, q.y));
}
__device__ __forceinline__ void ln2(uint32_t* h, uint32_t rr, uint32_t my, const A3& ma, int t) {
  const uint32_t nn = as_u(__hmul2(__hneg2(as_h2(my)), as_h2(rr)));
#pragma unroll
  for (int j = 0; j < 12; j++) { h[2 * j] = h2fma(h[2 * j], lo2(rr), lo2(nn)); h[2 * j + 1] = h2fma(h[2 * j + 1], hi2(rr), hi2(nn)); }
#pragma unroll
  for (int k = 0; k < 3; k++) { stsm4(ma.a[k] + t * kFrame, h + 8 * k); stsm4((ma.a[k] ^ 32) + t * kFrame, h + 8 * k + 4); }
}

__device__ __forceinline__ uint32_t ring_pos(uint32_t r) { return min(r, r - 196u); }
__device__ __forceinline__ uint32_t ring_row(uint32_t r) { return ((r * 1338u) >> 16) * (kBufStride - kChunk) + r * 64; }
__device__ __forceinline__ uint32_t ring_stat(uint32_t r) { return ((r * 1338u) >> 16) * (kBufStride - 49 * 4) + r * 4; }
__device__ __forceinline__ A3 t_in_addr(uint32_t sb, uint32_t r0, int lane) {
  return swz3(sb + kOffBuf + (lane & 3) * 16 + ring_row(ring_pos(r0 + (lane >> 2))));
}
__device__ __forceinline__ A3 t_out_addr(uint32_t sb, uint32_t r0, int lane) {
  return swz3(sb + kOffBuf + ((lane >> 3) & 1) * kFrame + (lane & 16) + ring_row(ring_pos(r0 + (lane & 7))));
}
__device__ __forceinline__ uint32_t t_stat_addr(uint32_t sb, uint32_t r0, int lane) {
  return sb + kOffBuf + kXBytes + (lane & 3) * kFrame + ring_stat(ring_pos(r0 + (lane >> 2)));
}
template <bool kDirect>
__device__ __forceinline__ void softmax4(uint32_t* s, uint32_t rhoA, uint32_t rhoB, uint32_t ro, float f) {
  if (kDirect) { s[0] = h2mul(s[0], rhoA); s[1] = h2mul(s[1], rhoB); }
  uint32_t mx = h2max(s[0], s[1]);
  mx = h2max(lo2(mx), hi2(mx));
  if (kDirect) {
    const uint32_t nm = as_u(__hmul2(__hneg2(as_h2(mx)), as_h2(ro)));
    s[0] = h2fma(s[0], ro, nm); s[1] = h2fma(s[1], ro, nm);
  } else {
    s[0] = h2mul(h2sub(s[0], mx), ro); s[1] = h2mul(h2sub(s[1], mx), ro);
  }
  s[0] = h2ex2(s[0]); s[1] = h2ex2(s[1]);
  uint32_t sm = h2add(s[0], s[1]);
  sm = h2add(lo2(sm), hi2(sm));
  const float iv = f * rcp_fast(__low2float(as_h2(sm)));
  const uint32_t inv = pack_h2(iv, iv);
  if (kDirect) { s[0] = h2mul(h2mul(s[0], rhoA), inv); s[1] = h2mul(h2mul(s[1], rhoB), inv); }
  else { s[0] = h2mul(s[0], inv); s[1] = h2mul(s[1], inv); }
}
template <bool kFirst>
__device__ __forceinline__ void mix(uint32_t* u, const uint32_t* z, uint32_t p0, uint32_t p1) {
#pragma unroll
  for (int j = 0; j < 12; j++) {
    u[2 * j] = h2fma(z[2 * j + 1], hi2(p0), kFirst ? h2mul(z[2 * j], lo2(p0)) : h2fma(z[2 * j], lo2(p0), u[2 * j]));
    u[2 * j + 1] = h2fma(z[2 * j + 1], hi2(p1), kFirst ? h2mul(z[2 * j], lo2(p1)) : h2fma(z[2 * j], lo2(p1), u[2 * j + 1]));
  }
}
template <bool kDirect>
__device__ __forceinline__ void put_stats(uint32_t sa, float sg, float mm, const Params& P) {
  const bool ok = (sg >= P.sgmin) & (kDirect || fmaf(sg, 9.8f, fabsf(mm)) < fmaf(P.kappa, -627.2f, 60000.f));
  const uint32_t sh = pack_h2(sg, mm), sw = pack_bf2(-sg, mm);
  asm volatile("st.shared.b32 [%0], %1;" ::"r"(sa), "r"(ok ? sh : sw) : "memory");
}

__device__ __forceinline__ bool task_T(uint32_t sb, uint32_t r0, uint32_t flag, int lane, const Params& P) {
  const int c = lane & 3;
  const uint32_t selK = (c & 1) ? 0x7632u : 0x5410u, selO = 0x1010u + c * 0x2222u;
  const uint64_t da = mk_desc(sb, 1), dw = mk_desc(sb + kOffWt, 1);
  uint32_t x[48], yA[24], yB[24], qA[26], qB[26], ssA, ssB;
  {
    const A3 la = t_in_addr(sb, r0, lane);
#pragma unroll
    for (int t = 0; t < 4; t++) load_row(x + 12 * t, la, t);
  }
  row_to_h2(yA, x); row_to_h2(yA + 1, x + 12);
  row_to_h2(yB, x + 24); row_to_h2(yB + 1, x + 36);
  ssB = sumsq<C1>(yB);
  ssA = sumsq<C1>(yA);
  if (SPL & 1) gemm_at2(qA, yA, da); else gemm_at(qA, yA, da);
  if (SPL & 2) gemm_at2(qB, yB, da); else gemm_at(qB, yB, da);
  ssB = quad_h2add(ssB);
  ssA = quad_h2add(ssA);
  uint32_t rA[2], rB[2];
  wg_wait<1>(); pin<26>(qA);
  const uint32_t myA = __byte_perm(qA[24], qA[25], 0x5410), nuA = __byte_perm(qA[24], qA[25], 0x7632);
  const uint32_t nsA = h2mul(myA, 0xd600d600u);
  const float2 ra = rstd(unpack_h2(h2fma(nsA, myA, ssA)));
  const uint32_t rhoA = pack_h2(ra.x, ra.y);
  rA[0] = scores(qA, yA, selK);
  sched_fence(rA[0], rhoA, 0);
  wg_wait<0>(); pin<26>(qB);
  const uint32_t myB = __byte_perm(qB[24], qB[25], 0x5410), nuB = __byte_perm(qB[24], qB[25], 0x7632);
  const uint32_t nsB = h2mul(myB, 0xd600d600u);
  const float2 rb = rstd(unpack_h2(h2fma(nsB, myB, ssB)));
  const uint32_t rhoB = pack_h2(rb.x, rb.y);
  const uint32_t ro = prmt(rhoA, rhoB, selO), mo = bitsel(prmt(myA, myB, selO), 0xffffu, 0x292e0000u);
  asm volatile("{\n.reg .pred p, q;\n.reg .b32 t;\nabs.f16x2 t, %1;\nsetp.gtu.f16x2 p|q, t, %2;\nor.pred p, p, q;\n@p st.volatile.shared.b32 [%0], %2;\n}"
               ::"r"(flag), "r"(h2fma(ro, mo, 0xbc190000u)), "r"(0x3c003c00u) : "memory");
  uint32_t mu;
  rA[1] = scores(qA, yB, selK); rB[0] = scores(qB, yA, selK); rB[1] = scores(qB, yB, selK);
  uint32_t p[8], s[2];
#pragma unroll
  for (int k = 0; k < 2; k++) s[k] = h2add((c & 2) ? rB[k] : rA[k], __shfl_xor_sync(0xffffffffu, (c & 2) ? rA[k] : rB[k], 2));
  softmax4<true>(s, rhoA, rhoB, ro, P.kt);
#pragma unroll
  for (int t = 0; t < 4; t++) { p[2 * t] = __shfl_sync(0xffffffffu, s[0], t, 4); p[2 * t + 1] = __shfl_sync(0xffffffffu, s[1], t, 4); }
  mu = h2fma(s[1], nuB, h2mul(s[0], nuA));
  mix<true>(qA, yA, p[0], p[2]); mix<false>(qA, yB, p[1], p[3]);
  mu = h2add(lo2(mu), hi2(mu));
  mix<true>(qB, yA, p[4], p[6]);
  gemm_w<1>(yA, qA, dw);
  sched_fence(0, 0, 0);
  mix<false>(qB, yB, p[5], p[7]);
  gemm_w<1>(yB, qB, dw);
  const A3 ma = t_out_addr(sb, r0, lane);
  wg_wait<1>(); pin<24>(yA);
  uint32_t bad;
  asm volatile("ld.shared.b32 %0, [%1];" : "=r"(bad) : "r"(flag + (yA[0] & (gridDim.x == 0x7fffffffu))) : "memory");
  float2 d = unpack_h2(h2fma(nsA, myA, quad_h2add(sumsq<C2>(yA))));
  if (UNLIKELY(__any_sync(0xffffffffu, !(d.x + d.y < 65000.f) | (bad != 0)))) {
    if (__any_sync(0xffffffffu, bad != 0)) {
      wg_wait<0>(); pin<24>(yB);
      return false;
    }
    d = var96_f32(yA, myA);
  }
  float2 r = rstd(make_float2(fabsf(d.x), fabsf(d.y)));
  const uint32_t rrA = pack_h2(r.x, r.y);
  ln2(yA, rrA, myA, ma, 0);
  wg_wait<0>(); pin<24>(yB);
  d = unpack_h2(h2fma(nsB, myB, quad_h2add(sumsq<C2>(yB))));
  if (UNLIKELY(__any_sync(0xffffffffu, !(d.x + d.y < 65000.f)))) d = var96_f32(yB, myB);
  r = rstd(make_float2(fabsf(d.x), fabsf(d.y)));
  const uint32_t rrB = pack_h2(r.x, r.y);
  ln2(yB, rrB, myB, ma, 2);
  put_stats<true>(t_stat_addr(sb, r0, lane), rcp_fast(__low2float(as_h2(prmt(rrA, rrB, selO)))), __low2float(as_h2(h2add(mo, mu))), P);
  return true;
}

__device__ __forceinline__ void task_T_general(uint32_t sb, uint32_t r0, const Params& P) {
  int lane;
  asm volatile("mov.u32 %0, %%laneid;" : "=r"(lane));
  const int c = lane & 3;
  const uint64_t da = mk_desc(sb, 1), dw = mk_desc(sb + kOffWt, 1);
  uint32_t yA[24], yB[24], qA[26], qB[26];
  float ieo, mo, ao;
  {
    float ie[4], m[4];
    const A3 la = t_in_addr(sb, r0, lane);
    ln1_f32(yA, la, 0, ie, m);
    ln1_f32(yB, la, 2, ie + 2, m + 2);
    const float2 na = sumsq_f32(yA), nb = sumsq_f32(yB);
    const float ik = 9.8f * rcp_fast(P.kt) * rsq_fast(fmaxf(fmaxf(fmaxf(na.x, na.y), fmaxf(nb.x, nb.y)), 2e-7f));
    ieo = (c & 2) ? ((c & 1) ? ie[3] : ie[2]) : ((c & 1) ? ie[1] : ie[0]);
    mo = (c & 2) ? ((c & 1) ? m[3] : m[2]) : ((c & 1) ? m[1] : m[0]);
    const bool lim = (ieo * P.kt > 400.f) & (ik < ieo);
    const float u = ik * rcp_fast(ieo);
    ao = lim ? u : 1.f; ieo = lim ? ik : ieo;
  }
  uint32_t rA[2], rB[2], s[2], p[8];
  const uint32_t selK = (c & 1) ? 0x7632u : 0x5410u;
  gemm_at(qA, yA, da);
  wg_wait<0>(); pin<26>(qA);
  const uint32_t nuA = __byte_perm(qA[24], qA[25], 0x7632);
  rA[0] = scores(qA, yA, selK); rA[1] = scores(qA, yB, selK);
  sched_fence(rA[0], rA[1], nuA);
  gemm_at(qB, yB, da);
  wg_wait<0>(); pin<26>(qB);
  const uint32_t nuB = __byte_perm(qB[24], qB[25], 0x7632);
  rB[0] = scores(qB, yA, selK); rB[1] = scores(qB, yB, selK);
#pragma unroll
  for (int k = 0; k < 2; k++) s[k] = h2add((c & 2) ? rB[k] : rA[k], __shfl_xor_sync(0xffffffffu, (c & 2) ? rA[k] : rB[k], 2));
  softmax4<false>(s, 0, 0, score_scale(&g_par.cS_t), P.kt * ieo);
  uint32_t mu = h2fma(s[1], nuB, h2mul(s[0], nuA));
  mu = h2add(lo2(mu), hi2(mu));
#pragma unroll
  for (int t = 0; t < 4; t++) { p[2 * t] = __shfl_sync(0xffffffffu, s[0], t, 4); p[2 * t + 1] = __shfl_sync(0xffffffffu, s[1], t, 4); }
  sched_fence(mu, 0, 0);
  mix<true>(qA, yA, p[0], p[2]); mix<false>(qA, yB, p[1], p[3]);
  mix<true>(qB, yA, p[4], p[6]); mix<false>(qB, yB, p[5], p[7]);
  const uint32_t ah = pack_h2(ao, ao);
#pragma unroll
  for (int t = 0; t < 4; t++) {
    const uint32_t a = __shfl_sync(0xffffffffu, ah, t, 4);
#pragma unroll
    for (int j = 0; j < 12; j++) asm volatile("mul.f16x2 %0, %0, %1;" : "+r"(((t & 2) ? yB : yA)[2 * j + (t & 1)]) : "r"(a));
  }
  gemm_w<1>(yA, qA, dw);
  gemm_w<1>(yB, qB, dw);
  wg_wait<0>(); pin<24>(yA); pin<24>(yB);
  asm volatile("mov.u32 %0, %%laneid;" : "=r"(lane));
  float ie[4];
#pragma unroll
  for (int t = 0; t < 4; t++) ie[t] = __shfl_sync(0xffffffffu, ieo, t, 4);
  const float2 da2 = sumsq_f32(yA), db2 = sumsq_f32(yB);
  const uint32_t rrA = pack_h2_sat(rsq_fast(fmaf(da2.x, 1.f / 96.f, 1e-5f * ie[0] * ie[0])), rsq_fast(fmaf(da2.y, 1.f / 96.f, 1e-5f * ie[1] * ie[1])));
  const uint32_t rrB = pack_h2_sat(rsq_fast(fmaf(db2.x, 1.f / 96.f, 1e-5f * ie[2] * ie[2])), rsq_fast(fmaf(db2.y, 1.f / 96.f, 1e-5f * ie[3] * ie[3])));
  const A3 ma = t_out_addr(sb, r0, lane);
  ln2(yA, rrA, 0u, ma, 0); ln2(yB, rrB, 0u, ma, 2);
  const float r = __low2float(as_h2(prmt(rrA, rrB, 0x1010u + (lane & 3) * 0x2222u))), sg = rcp_fast(r * ieo);
  put_stats<false>(t_stat_addr(sb, r0, lane), sg, fmaf(__low2float(as_h2(mu)) * r, sg, mo), P);
}

__device__ __forceinline__ void t_release(uint32_t sb, uint32_t ia, uint32_t ib, int lane) {
  asm volatile("fence.proxy.async.shared::cta;" ::: "memory");
  __syncwarp();
  asm volatile("{\n.reg .pred p;\nsetp.le.u32 p, %1, %2;\n@p mbarrier.arrive.shared::cta.b64 _, [%0];\n}"
               ::"r"(sb + kOffBar + 32 + ((ia + lane) & 3) * 8), "r"(lane), "r"(ib - ia) : "memory");
}
__device__ __forceinline__ void loop_T(uint32_t sb, int nw, int wg, int wp, int lane, const Params& P, bool direct) {
  const uint32_t barF = sb + kOffBar, flag = sb + kOffFlag + wg * 4;
  mbar_wait(sb + kOffBarW, 0);
  uint32_t r0 = 32 * wg + 8 * wp, par = 0;
  for (int k = (49 * nw + 63 - 32 * wg) >> 6; k > 0; k--) {
    const uint32_t ia = (r0 * 1338u) >> 16, ib = ((r0 + 7) * 1338u) >> 16;
    mbar_wait(barF + ia * 8, par);
    if (UNLIKELY(ib != ia)) mbar_wait(barF + (ib & 3) * 8, par ^ (ib >> 2));
    const uint32_t r = r0;
    r0 += 64;
    if (r0 >= 196) { r0 -= 196; par ^= 1; }
    if (LIKELY(direct)) {
      if (LIKELY(task_T(sb, r, flag, lane, P))) {
        t_release(sb, ia, ib, lane);
        continue;
      }
      asm volatile("barrier.cta.sync.aligned %0, 128;" ::"r"(wg + 1) : "memory");
      asm volatile("st.shared.b32 [%0], %1;\nfence.acq_rel.cta;" ::"r"(flag), "r"(0) : "memory");
    }
    task_T_general(sb, r, P);
    t_release(sb, ia, ib, lane);
  }
}

struct SFrame {
  uint32_t o0, o1;
  uint32_t t;
  uint32_t st;
  bool light;
};
__device__ __forceinline__ SFrame s_frame(int t, int wp, int lane, A3& ma) {
  SFrame f;
  const int rb = (wp + t) & 3;
  f.light = rb == 3;
  f.t = t;
  f.st = t * kFrame + kXBytes + rb * 64;
  ma = swz3(t * kFrame + rb * 1024 + ((lane * 65) & 0x3d0));
  if (f.light && (lane & 15)) ma.a[0] = ma.a[1] = ma.a[2] = kXBytes + 256;
  const uint32_t r = 16 * rb + (lane >> 2);
  f.o0 = (t * (kH * kW) + r + (r / 7) * (kW - 7)) * 192 + (lane & 3) * 16;
  f.o1 = (t * (kH * kW) + r + 8 + ((r + 8) / 7) * (kW - 7)) * 192 + (lane & 3) * 16;
  asm volatile("" : "+r"(f.o0), "+r"(f.o1));
  return f;
}
template <int kHi>
__device__ __forceinline__ void s_load(uint32_t (&v)[24], uint32_t buf, A3 ma) {
  asm volatile("" : "+r"(ma.a[0]), "+r"(ma.a[1]), "+r"(ma.a[2]));
#pragma unroll
  for (int k = 0; k < 3; k++) {
    const uint32_t a = kHi ? ma.a[k] >> 16 : ma.a[k] & 0xffffu;
    ldsm4(v + 8 * k, buf + a); ldsm4(v + 8 * k + 4, buf + (a ^ 32));
  }
}
__device__ __forceinline__ void gemm_s(uint32_t* s, const uint32_t* q, uint32_t pl) {
  const uint64_t dA = mk_desc(pl, 1);
  wg_fence();
  wg56h<0>(s, q, dA); wg56h<1>(s, q + 4, dA + 2);
  wg56h<1>(s, q + 8, dA + 196); wg56h<1>(s, q + 12, dA + 198);
  wg56h<1>(s, q + 16, dA + 392); wg56h<1>(s, q + 20, dA + 394);
  wg_commit();
}
template <bool kAll>
__device__ __forceinline__ void stg128(uint8_t* o, const uint32_t* w, uint32_t doit) {
  if (kAll) asm volatile("st.global.v4.b32 [%0], {%1,%2,%3,%4};" ::"l"(o), "r"(w[0]), "r"(w[1]), "r"(w[2]), "r"(w[3]) : "memory");
  else asm volatile("{\n.reg .pred p;\nsetp.ne.u32 p, %5, 0;\n@p st.global.v4.b32 [%0], {%1,%2,%3,%4};\n}" ::"l"(o), "r"(w[0]), "r"(w[1]), "r"(w[2]), "r"(w[3]), "r"(doit) : "memory");
}
template <int kRow, bool kAll>
__device__ __forceinline__ void s_store(const uint32_t (&v)[24], uint32_t e, uint8_t* o) {
  uint32_t w[12];
#pragma unroll
  for (int j = 0; j < 12; j += 2) {
    const float2 y = unpack_h2(h2fma(v[2 * j + kRow], lo2(e), hi2(e))), z = unpack_h2(h2fma(v[2 * j + 2 + kRow], lo2(e), hi2(e)));
    w[j] = pack_bf2(y.x, z.x); w[j + 1] = pack_bf2(y.y, z.y);
  }
#pragma unroll
  for (int i3 = 0; i3 < 3; i3++) stg128<kAll>(o + 64 * i3, w + 4 * i3, e);
}
template <int kRow, bool kAdd>
__device__ __forceinline__ void s_store_wide(const uint32_t (&v)[24], uint32_t e, uint8_t* o, const Params& P) {
  const float2 z = stat_f32(e);
#pragma unroll
  for (int i3 = 0; i3 < 3; i3++) {
    uint32_t w[4] = {0, 0, 0, 0};
    if (kAdd)
      asm volatile("{\n.reg .pred p;\nsetp.ne.u32 p, %5, 0;\n@p ld.global.v4.b32 {%0,%1,%2,%3}, [%4];\n}"
                   : "+r"(w[0]), "+r"(w[1]), "+r"(w[2]), "+r"(w[3]) : "l"(o + 64 * i3), "r"(e) : "memory");
#pragma unroll
    for (int j = 0; j < 4; j++) {
      const float2 ya = unpack_h2(v[8 * i3 + 2 * (j & 2) + kRow]), yb = unpack_h2(v[8 * i3 + 2 * (j & 2) + 2 + kRow]);
      const float2 y = (j & 1) ? make_float2(ya.y, yb.y) : make_float2(ya.x, yb.x);
      w[j] = kAdd ? pack_bf2(fmaf(y.x, P.kappa, __uint_as_float(w[j] << 16)), fmaf(y.y, P.kappa, __uint_as_float(w[j] & 0xffff0000u)))
                  : pack_bf2(fmaf(y.x, z.x, z.y), fmaf(y.y, z.x, z.y));
    }
    stg128<false>(o + 64 * i3, w, e);
  }
  __syncwarp();
}
__device__ __forceinline__ uint32_t ex2_pair(uint32_t s) {
  uint32_t lo, hi;
  asm volatile("{\n.reg .b16 a, b, c;\nmov.b32 {a, b}, %2;\nex2.approx.f16 c, a;\ncvt.u32.u16 %0, c;\nex2.approx.f16 c, b;\ncvt.u32.u16 %1, c;\n}"
               : "=r"(lo), "=r"(hi) : "r"(s));
  return lo + hi * 65536u;
}
__device__ __forceinline__ uint32_t ex2_lo(uint32_t s) {
  uint32_t lo;
  asm volatile("{\n.reg .b16 a, b, c;\nmov.b32 {a, b}, %1;\nex2.approx.f16 c, a;\ncvt.u32.u16 %0, c;\n}" : "=r"(lo) : "r"(s));
  return lo;
}

template <int kSecond>
__device__ __forceinline__ void step_S(uint32_t sb, uint32_t (&v)[24], uint32_t (&vn)[24], uint32_t (&q)[24], uint32_t (&s)[16], const SFrame& f,
                                       const SFrame& fn, const A3& ma, uint32_t i, int nw, uint32_t w, uint32_t wlast, uint8_t* ob, int lane, const Params& P,
                                       bool scaled, const CUtensorMap* tm) {
  const uint32_t ia = i & 3, ib = kSecond ? (i + 1) & 3 : ia;
  const uint32_t buf = sb + kOffBuf + ia * kBufStride, bufn = sb + kOffBuf + ib * kBufStride;
  const uint64_t dQ = mk_desc(sb + kOffAs, 1);
  const uint32_t never = gridDim.x == 0x7fffffffu;
  uint32_t p[16], u[24], e0, e1;
  const uint32_t sta = buf + f.st + (lane & 0x1c);
  asm volatile("ld.shared.b32 %0, [%1];" : "=r"(e0) : "r"(sta) : "memory");
  asm volatile("ld.shared.b32 %0, [%1];" : "=r"(e1) : "r"(sta + 32) : "memory");
  const uint32_t keep = (lane & 3) == 0 ? 0x0000ffffu : 0u;
  s[12] = bitsel(s[12], keep, 0xfc00fc00u); s[13] = bitsel(s[13], keep, 0xfc00fc00u);
  __half2 am = __hmax2(as_h2(s[12]), as_h2(s[13])), an = __hmax2(__habs2(as_h2(s[0])), __habs2(as_h2(s[1])));
#pragma unroll
  for (int j = 2; j < 7; j++) { am = __hmax2(am, __habs2(as_h2(s[j]))); an = __hmax2(an, __habs2(as_h2(s[j + 5]))); }
  bool ok = __hble2(__hmax2(am, an), as_h2(0x47004700u)) & !scaled;
  constexpr int kE = IL == 0 ? 12 : IL == 1 ? 4 : IL == 2 ? 0 : 8;
  p[12] = ex2_lo(s[12]); p[13] = ex2_lo(s[13]);
#pragma unroll
  for (int j = 0; j < kE; j++) p[j] = ex2_pair(s[j]);
  if (UNLIKELY(!__all_sync(0xffffffffu, ok))) {
    const uint32_t x0 = h2max(h2max(h2max(s[0], s[2]), h2max(s[4], s[6])), h2max(h2max(s[8], s[10]), s[12]));
    const uint32_t x1 = h2max(h2max(h2max(s[1], s[3]), h2max(s[5], s[7])), h2max(h2max(s[9], s[11]), s[13]));
    uint32_t mx = h2max(__byte_perm(x0, x1, 0x5410), __byte_perm(x0, x1, 0x7632));
    mx = h2max(mx, __shfl_xor_sync(0xffffffffu, mx, 1));
    mx = h2max(mx, __shfl_xor_sync(0xffffffffu, mx, 2));
    const uint32_t cs = score_scale(&g_par.cS_s);
#pragma unroll
    for (int j = 0; j < 7; j++) { s[2 * j] = h2mul(h2sub(s[2 * j], lo2(mx)), cs); s[2 * j + 1] = h2mul(h2sub(s[2 * j + 1], hi2(mx)), cs); }
    p[12] = ex2_lo(s[12]); p[13] = ex2_lo(s[13]);
#pragma unroll
    for (int j = 0; j < kE; j++) p[j] = ex2_pair(s[j]);
    ok = !never;
  }
  asm volatile("mov.b32 %0, 0;\nmov.b32 %1, 0;" : "=r"(p[14]), "=r"(p[15]));
  const uint64_t mn = mk_desc(buf + f.t * kFrame, kChunk >> 4);
  wg_fence();
  wg96h<2, 1>(q, p + 12, mn + 192, never); wg96h<1, 1>(q, p, mn);
#pragma unroll
  for (int j = 4; j < 12; j++) p[j] = ex2_pair(s[j]);
  const bool wide = __any_sync(0xffffffffu, ((e0 | e1) & 0x8000u) != 0u);
  uint32_t rs = fold_add(h2add(h2add(h2add(p[0], p[2]), p[12]), h2add(h2add(p[4], p[6]), h2add(p[8], p[10]))),
                         h2add(h2add(h2add(p[1], p[3]), p[13]), h2add(h2add(p[5], p[7]), h2add(p[9], p[11])))), rt;
  asm volatile("shfl.sync.bfly.b32 %0, %1, 1, 31, 0xffffffff;" : "=r"(rt) : "r"(rs));
  wg_fence();
  wg96h<1, 1>(q, p + 4, mn + 64); wg96h<1, 1>(q, p + 8, mn + 128);
  wg_commit();
  if (UNLIKELY(wide)) { s_store_wide<0, false>(v, e0, ob + f.o0, P); s_store_wide<1, false>(v, e1, ob + f.o1, P); }
  rs = h2add(rs, rt);
  asm volatile("shfl.sync.bfly.b32 %0, %1, 2, 31, 0xffffffff;" : "=r"(rt) : "r"(rs));
  if (!kSecond) s_load<1>(vn, bufn, ma);
  rs = h2add(rs, rt);
  const float d0 = __low2float(as_h2(rs)), d1 = __high2float(as_h2(rs));
  const float g0 = wide ? P.kappa : __low2float(as_h2(e0)), g1 = wide ? P.kappa : __low2float(as_h2(e1));
  const float c0 = P.kappa * rcp_fast(d0 * g0), c1 = P.kappa * rcp_fast(d1 * g1);
  uint32_t cb = pack_h2(e0 ? c0 : 0.f, e1 ? c1 : 0.f);
  wg_wait<0>(); pin<24>(q);
  auto refill = [&]() {
    if (f.light) {
      const uint32_t bar = sb + kOffBar + ia * 8;
      if (lane == 0) {
        if (i + 4 <= nw) tma_load(buf + f.t * kFrame, tm, bar, i + 5 >= nw ? wlast : w + 4 * gridDim.x, f.t);
      }
      __syncwarp();
    }
  };
#pragma unroll
  for (int j = 0; j < 12; j++) { u[2 * j] = h2mul(q[2 * j], lo2(cb)); u[2 * j + 1] = h2mul(q[2 * j + 1], hi2(cb)); }
  gemm_w<2>(v, u, dQ + (kWMat >> 4), !wide);
  if (RF == 0 || (RF == 1 && kSecond)) refill();
  if (kSecond) {
    if (i + 1 < nw) mbar_wait(sb + kOffBar + 32 + ib * 8, ((i + 1) >> 2) & 1);
    s_load<0>(vn, bufn, ma);
  }
  gemm_w<2>(q, vn, dQ, never);
  if (RF == 2 || (RF == 1 && !kSecond)) refill();
  const bool plain = !(wide | f.light);
  wg_wait<1>(); pin<24>(v);
  if (LIKELY(plain)) s_store<0, true>(v, e0, ob + f.o0);
  wg_wait<0>(); pin<24>(q);
  gemm_s(s, q, bufn + fn.t * kFrame);
  if (LIKELY(plain)) s_store<1, true>(v, e1, ob + f.o1);
  else if (!wide) { s_store<0, false>(v, e0, ob + f.o0); __syncwarp(); }
  else if (wide) { s_store_wide<0, true>(v, e0, ob + f.o0, P); s_store_wide<1, true>(v, e1, ob + f.o1, P); }
  wg_wait<0>(); pin<14>(s);
}

__device__ __forceinline__ void loop_S(uint32_t sb, int nw, bool half, uint32_t wlast, int t0, int wp, int lane, const Params& P, bool scaled,
                                       const CUtensorMap* tm, uint8_t* __restrict__ out) {
  A3 ma, mb;
  const SFrame f0 = s_frame(t0, wp, lane, ma), f1 = s_frame(t0 ^ 2, wp, lane, mb);
#pragma unroll
  for (int k = 0; k < 3; k++) ma.a[k] += mb.a[k] << 16;
  uint32_t v0[24], v1[24], q[24], s[16];
  mbar_wait(sb + kOffBarW + 8, 0);
  mbar_wait(sb + kOffBar + 32, 0);
  s_load<0>(v0, sb + kOffBuf, ma);
  gemm_w<0>(q, v0, mk_desc(sb + kOffAs, 1));
  wg_wait<0>(); pin<24>(q);
  gemm_s(s, q, sb + kOffBuf + f0.t * kFrame);
  wg_wait<0>(); pin<14>(s);
  uint32_t w = blockIdx.x;
  for (uint32_t i = 0; i < nw; i++, w += gridDim.x) {
    if (i + 1 == nw) w = wlast;
    const uint32_t wy = (w * 57457u) >> 22;
    uint8_t* ob = out + (size_t)((wy * (7 * kW - 7 * kNWX) + w * 7) * 192u);
    asm volatile("" : "+l"(ob));
    step_S<0>(sb, v0, v1, q, s, f0, f1, ma, i, nw, w, wlast, ob, lane, P, scaled, tm);
    if (half && i + 1 == nw) break;
    step_S<1>(sb, v1, v0, q, s, f1, f0, ma, i, nw, w, wlast, ob, lane, P, scaled, tm);
  }
  mbar_wait(sb + kOffBar + (nw & 3) * 8, (nw >> 2) & 1);
}

__global__ void __launch_bounds__(LB, 1) swin_main(const __grid_constant__ CUtensorMap tm, uint8_t* __restrict__ out) {
  extern __shared__ __align__(1024) uint8_t smem[];
  const uint32_t sb = smem_u32(smem);
  const int tid = threadIdx.x;
  const int wg = __shfl_sync(0xffffffffu, tid >> 7, 0);
  const int wp = __shfl_sync(0xffffffffu, (tid >> 5) & 3, 0);
  const int lane = tid & 31;
  const int b = blockIdx.x, nb = gridDim.x;
  const int nfull = kNWIN / nb, nrem = kNWIN - nfull * nb;
  const bool share = 2 * nrem <= nb;
  const int nw = nfull + (b < (share ? 2 * nrem : nrem));
  const bool half = share && nw > nfull;
  const uint32_t wlast = half && b >= nrem ? b - nrem + nfull * nb : b + (nw - 1) * nb;
  const uint32_t tshift = half && b >= nrem ? 2 : 0;
  if (tid == 0) {
    if ((sb & 1023) || nw < 5) __trap();
#pragma unroll
    for (int i = 0; i < 4; i++) {
      mbar_init(sb + kOffBar + i * 8, 4);
      mbar_init(sb + kOffBar + 32 + i * 8, 7);
    }
    asm volatile("st.shared.v2.b32 [%0], {%1,%1};" ::"r"(sb + kOffFlag), "r"(0) : "memory");
    mbar_init(sb + kOffBarW, 1); mbar_init(sb + kOffBarW + 8, 1);
    asm volatile("fence.mbarrier_init.release.cluster;" ::: "memory");
  }
  if (tid >= 128 && tid < 488) {
    const uint32_t e = tid - 128, fr = min(e / 20, 15u);
    asm volatile("st.shared.v4.b32 [%0], {%1,%1,%1,%1};" ::"r"(sb + kOffBuf + fr * kFrame + kXBytes + (e - fr * 20) * 16), "r"(0) : "memory");
    asm volatile("fence.proxy.async.shared::cta;" ::: "memory");
  }
#pragma unroll
  for (int i = 0; i < PAD; i++) sched_fence(tid + i, 0, 0);
  __syncthreads();
  if (lane == 0 && wg < 2) tma_load(sb + kOffBuf + (tid >> 5) * kFrame, &tm, sb + kOffBar + wg * 8, b + wg * nb, wp);
  __syncwarp();
  asm volatile("griddepcontrol.wait;" ::: "memory");
  if (tid == 0) {
    asm volatile("fence.proxy.async.global;" ::: "memory");
#pragma unroll
    for (int i = 0; i < 2; i++) {
      const uint32_t o = i ? kOffAs : 0, n = i ? kWBytes - kOffAs : kOffAs, bar = sb + kOffBarW + 8 * i;
      mbar_expect(bar, n);
      asm volatile("cp.async.bulk.shared::cluster.global.mbarrier::complete_tx::bytes [%0], [%1], %2, [%3];"
                   ::"r"(sb + o), "l"(reinterpret_cast<const uint8_t*>(g_wimg) + o), "r"(n), "r"(bar) : "memory");
    }
  }
  __syncwarp();
  if (wg >= 2) {
    if (WS) mbar_wait(sb + kOffBarW, 0);
    if (lane == 0) tma_load(sb + kOffBuf + (tid >> 5) * kFrame, &tm, sb + kOffBar + wg * 8, b + wg * nb, wp);
    __syncwarp();
  }
  Params P;
  {
    const float4 p0 = __ldcg(reinterpret_cast<const float4*>(&g_par));
    P.cS_t = p0.x; P.cS_s = p0.y; P.kt = p0.z; P.kappa = p0.w;
    P.sgmin = fmaxf(0.0045f, P.kappa * 0.011f);
  }
  const bool scaled = __any_sync(0xffffffffu, P.cS_s != 1.f);
  const bool direct = __all_sync(0xffffffffu, (P.cS_t == 1.f) & (P.kt <= 256.f) & (P.kappa <= 16.f));
  const int widx = __popc(((ROLE >> wg) & 1 ? ROLE : ~ROLE) & ((1 << wg) - 1));
  if ((ROLE >> wg) & 1) {
    loop_T(sb, nw, widx, wp, lane, P, direct);
  } else {
    loop_S(sb, nw, half, wlast, widx + tshift, wp, lane, P, scaled, &tm, out);
  }
}

__device__ __forceinline__ int ch_pos(int ch) { return 32 * (ch >> 5) + 4 * (ch & 4) + 8 * (ch & 1) + 2 * ((ch >> 3) & 3) + ((ch >> 1) & 1); }
__device__ __forceinline__ float pow2_ceil(float v) {
  return __uint_as_float((__float_as_uint(v) + 0x7fffffu) & 0x7f800000u);
}

constexpr int kPrepSplit = 12;
constexpr int kPrepThreads = 384;
__global__ void __launch_bounds__(kPrepThreads) swin_prep(const __nv_bfloat16* __restrict__ wqkv_t, const __nv_bfloat16* __restrict__ wo_t,
                                                          const __nv_bfloat16* __restrict__ wqkv_s, const __nv_bfloat16* __restrict__ wo_s) {
  asm volatile("griddepcontrol.launch_dependents;");
  __shared__ __align__(16) uint32_t raw[2][96][52];
  __shared__ __align__(16) uint32_t mu[3][52];
  __shared__ float nrm[12], nrm2[6], csum[6][9];
  const int mat = blockIdx.x / kPrepSplit, blk = blockIdx.x % kPrepSplit;
  const int tid = threadIdx.x, lane = tid & 31, warp = tid >> 5, g = lane >> 2, c = lane & 3;
  const __nv_bfloat16* wqkv = mat < 2 ? wqkv_t : wqkv_s;
  const __nv_bfloat16* wo = mat < 2 ? wo_t : wo_s;
  const bool isA = (mat & 1) == 0;
  {
    uint4 v[3], u[3];
#pragma unroll
    for (int q = 0; q < 3; q++) {
      const int e = tid + q * kPrepThreads, i = e / 12, c8 = (e % 12) * 8;
      v[q] = __ldg(reinterpret_cast<const uint4*>(wqkv + i * 288 + (isA ? 0 : 192) + c8));
      u[q] = __ldg(reinterpret_cast<const uint4*>(isA ? wqkv + i * 288 + 96 + c8 : wo + i * 96 + c8));
    }
#pragma unroll
    for (int q = 0; q < 3; q++) {
      const int e = tid + q * kPrepThreads, i = e / 12, c4 = (e % 12) * 4;
      *reinterpret_cast<uint4*>(&raw[0][i][c4]) = v[q];
      *reinterpret_cast<uint4*>(&raw[1][i][c4]) = u[q];
    }
  }
  __syncthreads();
  {
    const int m = warp / 6, cp = (warp % 6) * 8 + g;
    float s0 = 0.f, s1 = 0.f, q0 = 0.f, q1 = 0.f;
#pragma unroll
    for (int i = 0; i < 24; i++) {
      const uint32_t w = raw[m][4 * i + c][cp];
      const float lo = __uint_as_float(w << 16), hi = __uint_as_float(w & 0xffff0000u);
      s0 += lo; s1 += hi; q0 = fmaf(lo, lo, q0); q1 = fmaf(hi, hi, q1);
    }
    s0 = quad_sum(s0) * (1.f / 96.f); s1 = quad_sum(s1) * (1.f / 96.f); q0 = quad_sum(q0); q1 = quad_sum(q1);
    if (mat == 1 && m == 1) {
      float r0 = 0.f, r1 = 0.f;
#pragma unroll
      for (int i = 0; i < 12; i++) {
        const uint32_t w0 = raw[1][2 * cp][4 * i + c], w1 = raw[1][2 * cp + 1][4 * i + c];
        r0 += __uint_as_float(w0 << 16) + __uint_as_float(w0 & 0xffff0000u);
        r1 += __uint_as_float(w1 << 16) + __uint_as_float(w1 & 0xffff0000u);
      }
      r0 = quad_sum(r0) * (1.f / 96.f); r1 = quad_sum(r1) * (1.f / 96.f);
      s0 = r0; s1 = r1;
    }
    if (m == 1 && c == 0) {
      const uint32_t hi = mat == 3 ? 0u : pack_bf2(s0, s1);
      mu[0][cp] = hi;
      mu[1][cp] = mat == 3 ? 0u : pack_bf2(s0 - __uint_as_float(hi << 16), s1 - __uint_as_float(hi & 0xffff0000u));
      mu[2][cp] = 0u;
    }
    if (m == 0 || isA) {
      q0 = fmaxf(fmaf(-96.f * s0, s0, q0), 0.f) + q0 * 1e-6f;
      q1 = fmaxf(fmaf(-96.f * s1, s1, q1), 0.f) + q1 * 1e-6f;
    }
    const bool usemax = m == 1 && mat == 3;
    float t = usemax ? fmaxf(q0, q1) : q0 + q1;
#pragma unroll
    for (int o = 4; o < 32; o <<= 1) { const float z = __shfl_xor_sync(0xffffffffu, t, o); t = usemax ? fmaxf(t, z) : t + z; }
    if (lane == 0) nrm[warp] = t;
  }
  __syncthreads();
  if (warp >= 6) return;
  float d[4] = {0.f, 0.f, 0.f, 0.f}, e[4] = {0.f, 0.f, 0.f, 0.f}, v0, v1;
  {
    const uint32_t arow = smem_u32(&raw[0][16 * warp + (lane & 15)][(lane >> 4) * 4]);
    const uint32_t brow = isA ? smem_u32(&raw[1][blk * 8 + (lane & 7)][(lane >> 3) * 4]) : smem_u32(&raw[1][lane][blk * 4]);
    const uint32_t mrow = smem_u32(&mu[min(lane & 7, 2)][(lane >> 3) * 4]);
#pragma unroll
    for (int k2 = 0; k2 < 3; k2++) {
      uint32_t b[4], m[4];
      if (isA) ldsm4(b, brow + k2 * 64);
      else asm volatile("ldmatrix.sync.aligned.m8n8.x4.trans.shared.b16 {%0,%1,%2,%3}, [%4];"
                        : "=r"(b[0]), "=r"(b[1]), "=r"(b[2]), "=r"(b[3]) : "r"(brow + k2 * (32 * 208)) : "memory");
      ldsm4(m, mrow + k2 * 64);
#pragma unroll
      for (int hf = 0; hf < 2; hf++) {
        uint32_t a[4];
        ldsm4(a, arow + (2 * k2 + hf) * 32);
        asm volatile("mma.sync.aligned.m16n8k16.row.col.f32.bf16.bf16.f32 {%0,%1,%2,%3},{%4,%5,%6,%7},{%8,%9},{%0,%1,%2,%3};"
                     : "+f"(d[0]), "+f"(d[1]), "+f"(d[2]), "+f"(d[3])
                     : "r"(a[0]), "r"(a[1]), "r"(a[2]), "r"(a[3]), "r"(b[2 * hf]), "r"(b[2 * hf + 1]));
        asm volatile("mma.sync.aligned.m16n8k16.row.col.f32.bf16.bf16.f32 {%0,%1,%2,%3},{%4,%5,%6,%7},{%8,%9},{%0,%1,%2,%3};"
                     : "+f"(e[0]), "+f"(e[1]), "+f"(e[2]), "+f"(e[3])
                     : "r"(a[0]), "r"(a[1]), "r"(a[2]), "r"(a[3]), "r"(m[2 * hf]), "r"(m[2 * hf + 1]));
      }
    }
    v0 = __shfl_sync(0xffffffffu, e[0] + e[1], lane & ~3); v1 = __shfl_sync(0xffffffffu, e[2] + e[3], lane & ~3);
    d[0] -= v0; d[1] -= v0; d[2] -= v1; d[3] -= v1;
    float t0 = d[0] + d[2], t1 = d[1] + d[3], t2 = v0 + v1;
#pragma unroll
    for (int o = 4; o < 32; o <<= 1) {
      t0 += __shfl_xor_sync(0xffffffffu, t0, o); t1 += __shfl_xor_sync(0xffffffffu, t1, o); t2 += __shfl_xor_sync(0xffffffffu, t2, o);
    }
    if (g == 0) { csum[warp][2 * c] = t0; csum[warp][2 * c + 1] = t1; csum[warp][8] = t2; }
  }
  const float nl = nrm[0] + nrm[1] + nrm[2] + nrm[3] + nrm[4] + nrm[5];
  const float nr = mat == 3 ? fmaxf(fmaxf(fmaxf(nrm[6], nrm[7]), fmaxf(nrm[8], nrm[9])), fmaxf(nrm[10], nrm[11]))
                            : nrm[6] + nrm[7] + nrm[8] + nrm[9] + nrm[10] + nrm[11];
  const float bound = __fsqrt_rn(nl) * __fsqrt_rn(nr) * 1.01f;
  const float f = isA ? 0.14724448f : 1.f;
  float sc = pow2_ceil(fmaxf(bound * (isA ? 0.14724448f / 160.f : mat == 1 ? 1.f / 16.f : 1.f / 64.f), 1e-30f));
  if (isA) sc = fminf(fmaxf(sc, 1.f), 32768.f);
  const float mul = f * __uint_as_float(0x7f000000u - __float_as_uint(sc));
  if (blk == 0 && tid == 0) (mat == 0 ? g_par.cS_t : mat == 1 ? g_par.kt : mat == 2 ? g_par.cS_s : g_par.kappa) = sc;
  asm volatile("bar.sync 1, 192;" ::: "memory");
  float mean[2];
#pragma unroll
  for (int b = 0; b < 2; b++)
    mean[b] = (csum[0][2 * c + b] + csum[1][2 * c + b] + csum[2][2 * c + b] + csum[3][2 * c + b] + csum[4][2 * c + b] + csum[5][2 * c + b]) *
              (1.f / 96.f);
  uint8_t* img = reinterpret_cast<uint8_t*>(g_wimg) + (mat == 0 ? 0 : mat == 1 ? kOffWt : mat == 2 ? kOffAs : kOffWs);
  const float vmean = (csum[0][8] + csum[1][8] + csum[2][8] + csum[3][8] + csum[4][8] + csum[5][8]) * (1.f / 96.f);
  float off = 0.f;
  if (mat == 2) {
    float q2 = 0.f;
#pragma unroll
    for (int q = 0; q < 4; q++) q2 = fmaf(d[q] - mean[q & 1], d[q] - mean[q & 1], q2);
#pragma unroll
    for (int o = 16; o; o >>= 1) q2 += __shfl_xor_sync(0xffffffffu, q2, o);
    if (lane == 0) nrm2[warp] = q2;
    asm volatile("bar.sync 1, 192;" ::: "memory");
    q2 = nrm2[0] + nrm2[1] + nrm2[2] + nrm2[3] + nrm2[4] + nrm2[5];
    off = 1.5f * pow2_ceil(fmaxf(__fsqrt_rn(q2 * (1.f / 768.f)) * mul * 3.f, 1e-4f));
  }
#pragma unroll
  for (int q = 0; q < 4; q++) {
    const int kp = ch_pos(16 * warp + g + 8 * (q >> 1)), np = ch_pos(blk * 8 + 2 * c + (q & 1));
    const uint32_t ko = (kp >> 5) * (mat == 0 ? kAtChunk : 6144) + (kp & 31) * 2;
    uint32_t a = ko + np * 64;
    a ^= ((a >> 7) & 3) << 4;
    float o = (d[q] - mean[q & 1]) * mul;
    o = mat == 2 ? o + off : __uint_as_float((__float_as_uint(o) + 0x8000u) & 0xffff0000u);
    *reinterpret_cast<__half*>(img + a) = __float2half_rn(o);
    if (mat == 1 && blk == 0) {
      a = (kp >> 5) * kAtChunk + (kp & 31) * 2 + (96 + 2 * c + (q & 1)) * 64;
      a ^= ((a >> 7) & 3) << 4;
      *reinterpret_cast<__half*>(reinterpret_cast<uint8_t*>(g_wimg) + a) = __float2half_rn((q & 1) ? ((q >> 1 ? v1 : v0) - vmean) * mul : 1.f / 96.f);
    }
  }
}

typedef CUresult (*EncodeFn)(CUtensorMap*, CUtensorMapDataType, cuuint32_t, void*, const cuuint64_t*, const cuuint64_t*,
                             const cuuint32_t*, const cuuint32_t*, CUtensorMapInterleave, CUtensorMapSwizzle,
                             CUtensorMapL2promotion, CUtensorMapFloatOOBfill);

}

extern "C" void kernel_launch(void* const* d_in, const int* in_sizes, int n_in, void* d_out, int out_size) {
  (void)in_sizes; (void)n_in; (void)out_size;
  static EncodeFn enc = nullptr;
  static int nsm = 0;
  if (!enc) {
    void* fn = nullptr;
    cudaDriverEntryPointQueryResult qr;
    cudaGetDriverEntryPoint("cuTensorMapEncodeTiled", &fn, cudaEnableDefault, &qr);
    enc = reinterpret_cast<EncodeFn>(fn);
    int dev = 0;
    cudaGetDevice(&dev);
    cudaDeviceGetAttribute(&nsm, cudaDevAttrMultiProcessorCount, dev);
    cudaFuncSetAttribute(swin_main, cudaFuncAttributeMaxDynamicSharedMemorySize, kSmemBytes);
  }
  CUtensorMap tm;
  const cuuint64_t dims[5] = {32, kW, kH, kT, 3};
  const cuuint64_t strides[4] = {192, 192ull * kW, 192ull * kW * kH, 64};
  const cuuint32_t box[5] = {32, 7, 7, 1, 3};
  const cuuint32_t es[5] = {1, 1, 1, 1, 1};
  enc(&tm, CU_TENSOR_MAP_DATA_TYPE_BFLOAT16, 5, d_in[0], dims, strides, box, es, CU_TENSOR_MAP_INTERLEAVE_NONE,
      CU_TENSOR_MAP_SWIZZLE_64B, CU_TENSOR_MAP_L2_PROMOTION_L2_128B, CU_TENSOR_MAP_FLOAT_OOB_FILL_NONE);

  cudaStream_t st = cudaStreamPerThread;
  swin_prep<<<4 * kPrepSplit, kPrepThreads, 0, st>>>(
      static_cast<const __nv_bfloat16*>(d_in[1]), static_cast<const __nv_bfloat16*>(d_in[2]),
      static_cast<const __nv_bfloat16*>(d_in[3]), static_cast<const __nv_bfloat16*>(d_in[4]));

  cudaLaunchConfig_t cfg = {};
  cfg.gridDim = dim3(nsm);
  cfg.blockDim = dim3(kNWG * 128);
  cfg.dynamicSmemBytes = kSmemBytes;
  cfg.stream = st;
  cudaLaunchAttribute at[1];
  at[0].id = cudaLaunchAttributeProgrammaticStreamSerialization;
  at[0].val.programmaticStreamSerializationAllowed = 1;
  cfg.attrs = at;
  cfg.numAttrs = 1;
  cudaLaunchKernelEx(&cfg, swin_main, tm, static_cast<uint8_t*>(d_out));
}
```

```cpp
#include <cuda_runtime.h>
#include <cuda.h>
#include <cuda_bf16.h>
#include <cuda_fp16.h>
#include <stdint.h>

#define LB 512
#define SF 17
#define TIE 0
#define SG 1
#define IL 1
#define FP 2
#define ROLE 3
#define RF 1
#define CK0 0
#define LIKELY(x) __builtin_expect(!!(x), 1)
#define UNLIKELY(x) __builtin_expect(!!(x), 0)
#define CV 1
#define C1 2
#define C2 2
#define WS 1
#define TL 1
#define PAD 0
#define SPL 1
#define SPN 64
#define SPO 1
#define LD 1
#define DA 1
#define E1 0
#define E2 0
#define E3 0
#define E4 0
#define G4 0
#define BE 0
#define CS 0
#define QP 0
#define PG 3
#define PR 4
#define PF0 1
#define EARLY 0
#define PF 2
#define HQ 0
#define PW 1
#define PRM 2
namespace {

constexpr int kH = 511, kW = 511, kT = 4;
constexpr int kNWX = 73, kNWIN = 73 * 73;
constexpr int kChunk = 3136;
constexpr int kXBytes = 3 * kChunk;
constexpr int kFrame = 9728;
constexpr int kBufStride = 4 * kFrame;
constexpr int kWMat = 18432;
constexpr int kAtChunk = 104 * 64;
constexpr int kOffWt = 3 * kAtChunk;
constexpr int kOffAs = kOffWt + kWMat, kOffWs = kOffAs + kWMat;
constexpr int kWBytes = kOffWs + kWMat;
constexpr int kOffBuf = kWBytes;
constexpr int kOffBar = kOffBuf + 4 * kBufStride + 640;
constexpr int kOffFlag = kOffBar + 64;
constexpr int kOffBarW = kOffBar + 80;
constexpr int kOffBarB = kOffBar + 96;
constexpr int kSmemBytes = kOffBar + 128;
constexpr int kNWG = 4;

struct Maps { CUtensorMap tm, pf; };
struct Params {
  float cS_t, cS_s;
  float kt;
  float kappa;
  float sgmin;
};

__device__ uint4 g_wimg[kWBytes / 16];
__device__ __align__(16) Params g_par;

#define TR(idx)
#define TRARG
#define TRPASS(x)
__device__ __forceinline__ uint32_t smem_u32(const void* p) { return (uint32_t)__cvta_generic_to_shared(p); }
__device__ __forceinline__ void mbar_init(uint32_t a, int c) { asm volatile("mbarrier.init.shared::cta.b64 [%0], %1;" ::"r"(a), "r"(c)); }
__device__ __forceinline__ void mbar_expect(uint32_t a, int bytes) {
  asm volatile("mbarrier.arrive.expect_tx.shared::cta.b64 _, [%0], %1;" ::"r"(a), "r"(bytes) : "memory");
}
__device__ __forceinline__ void mbar_arrive(uint32_t a) {
  asm volatile("mbarrier.arrive.shared::cta.b64 _, [%0];" ::"r"(a) : "memory");
}
__device__ __forceinline__ void mbar_wait(uint32_t a, uint32_t par) {
  asm volatile(
      "{\n.reg .pred p;\n.reg .u32 n;\n"
      "mbarrier.try_wait.parity.shared::cta.b64 p, [%0], %1;\n"
      "@p bra.uni WDONE;\n"
      "mov.u32 n, 0;\n"
      "WLOOP:\n"
      "mbarrier.try_wait.parity.shared::cta.b64 p, [%0], %1;\n"
      "@p bra.uni WDONE;\n"
      "add.u32 n, n, 1;\n"
      "setp.lt.u32 p, n, 0x1000000;\n"
      "@p bra.uni WLOOP;\n"
      "trap;\n"
      "WDONE:\n}" ::"r"(a), "r"(par) : "memory");
}
__device__ __forceinline__ void tma_load(uint32_t dst, const CUtensorMap* m, uint32_t bar, uint32_t w, uint32_t t) {
  const uint32_t wy = (w * 57457u) >> 22, wx = w - wy * kNWX;
  mbar_expect(bar, kXBytes);
  asm volatile(
      "cp.async.bulk.tensor.5d.shared::cluster.global.mbarrier::complete_tx::bytes [%0], [%1, {%3,%4,%5,%6,%3}], [%2];" ::"r"(dst),
      "l"(m), "r"(bar), "r"(0), "r"(wx * 7), "r"(wy * 7), "r"(t)
      : "memory");
}
__device__ __forceinline__ void tma_prefetch(const CUtensorMap* m, uint32_t w, uint32_t t) {
  const uint32_t wy = (w * 57457u) >> 22, wx = w - wy * kNWX;
  asm volatile("cp.async.bulk.prefetch.tensor.3d.L2.global [%0, {%1,%2,%3}];" ::"l"(m + 1), "r"(wx * 168), "r"(wy * 7), "r"(t) : "memory");
}
__device__ __forceinline__ void wg_fence() { asm volatile("wgmma.fence.sync.aligned;" ::: "memory"); }
__device__ __forceinline__ void wg_commit() { asm volatile("wgmma.commit_group.sync.aligned;" ::: "memory"); }
template <int N>
__device__ __forceinline__ void wg_wait() { asm volatile("wgmma.wait_group.sync.aligned %0;" ::"n"(N) : "memory"); }
template <int N>
__device__ __forceinline__ void pin(uint32_t* d) {
#pragma unroll
  for (int i = 0; i < N; i++) asm volatile("" : "+r"(d[i])::"memory");
}
__device__ __forceinline__ void sched_fence(uint32_t a, uint32_t b, uint32_t c) {
  asm volatile("{\n.reg .pred p;\n.reg .b32 t;\nsetp.ne.u32 p, %0, 0x7fffffff;\n@p bra.uni SFD;\n"
               "add.u32 t, %1, %2;\nadd.u32 t, t, %3;\nnanosleep.u32 t;\nSFD:\n}" ::"r"(gridDim.x), "r"(a), "r"(b), "r"(c) : "memory");
}
__device__ __forceinline__ uint64_t mk_desc(uint32_t addr, uint32_t lbo16) {
  return ((uint64_t)0x80000020u << 32) | ((addr >> 4) & 0x3fff) | (lbo16 << 16);
}

#define R4(d, i) "+r"(d[i]), "+r"(d[i + 1]), "+r"(d[i + 2]), "+r"(d[i + 3])
#define O4(d, i) "=r"(d[i]), "=r"(d[i + 1]), "=r"(d[i + 2]), "=r"(d[i + 3])
#define D24 "{%0,%1,%2,%3,%4,%5,%6,%7,%8,%9,%10,%11,%12,%13,%14,%15,%16,%17,%18,%19,%20,%21,%22,%23},"
#define D14 "{%0,%1,%2,%3,%4,%5,%6,%7,%8,%9,%10,%11,%12,%13},"

template <int SC, int TB>
__device__ __forceinline__ void wg96h(uint32_t (&d)[24], const uint32_t* a, uint64_t db, uint32_t acc = 0) {
  if (SC == 2)
    asm volatile("{\n.reg .pred p;\nsetp.ne.u32 p, %30, 0;\n"
                 "wgmma.mma_async.sync.aligned.m64n96k16.f16.f16.f16 " D24 "{%24,%25,%26,%27}, %28, p, 1, 1, %29;\n}"
                 : R4(d, 0), R4(d, 4), R4(d, 8), R4(d, 12), R4(d, 16), R4(d, 20)
                 : "r"(a[0]), "r"(a[1]), "r"(a[2]), "r"(a[3]), "l"(db), "n"(TB), "r"(acc));
  else if (SC)
    asm volatile("wgmma.mma_async.sync.aligned.m64n96k16.f16.f16.f16 " D24 "{%24,%25,%26,%27}, %28, 1, 1, 1, %29;"
                 : R4(d, 0), R4(d, 4), R4(d, 8), R4(d, 12), R4(d, 16), R4(d, 20)
                 : "r"(a[0]), "r"(a[1]), "r"(a[2]), "r"(a[3]), "l"(db), "n"(TB));
  else
    asm volatile("wgmma.mma_async.sync.aligned.m64n96k16.f16.f16.f16 " D24 "{%24,%25,%26,%27}, %28, 0, 1, 1, %29;"
                 : O4(d, 0), O4(d, 4), O4(d, 8), O4(d, 12), O4(d, 16), O4(d, 20)
                 : "r"(a[0]), "r"(a[1]), "r"(a[2]), "r"(a[3]), "l"(db), "n"(TB));
}
template <int SC>
__device__ __forceinline__ void wg104h(uint32_t (&d)[26], const uint32_t* a, uint64_t db) {
  if (SC)
    asm volatile("wgmma.mma_async.sync.aligned.m64n104k16.f16.f16.f16 "
                 "{%0,%1,%2,%3,%4,%5,%6,%7,%8,%9,%10,%11,%12,%13,%14,%15,%16,%17,%18,%19,%20,%21,%22,%23,%24,%25},"
                 "{%26,%27,%28,%29}, %30, 1, 1, 1, 0;"
                 : R4(d, 0), R4(d, 4), R4(d, 8), R4(d, 12), R4(d, 16), R4(d, 20), "+r"(d[24]), "+r"(d[25])
                 : "r"(a[0]), "r"(a[1]), "r"(a[2]), "r"(a[3]), "l"(db));
  else
    asm volatile("wgmma.mma_async.sync.aligned.m64n104k16.f16.f16.f16 "
                 "{%0,%1,%2,%3,%4,%5,%6,%7,%8,%9,%10,%11,%12,%13,%14,%15,%16,%17,%18,%19,%20,%21,%22,%23,%24,%25},"
                 "{%26,%27,%28,%29}, %30, 0, 1, 1, 0;"
                 : O4(d, 0), O4(d, 4), O4(d, 8), O4(d, 12), O4(d, 16), O4(d, 20), "=r"(d[24]), "=r"(d[25])
                 : "r"(a[0]), "r"(a[1]), "r"(a[2]), "r"(a[3]), "l"(db));
}
template <int SC>
__device__ __forceinline__ void wg56h(uint32_t* d, const uint32_t* a, uint64_t db) {
  if (SC)
    asm volatile("wgmma.mma_async.sync.aligned.m64n56k16.f16.f16.f16 " D14 "{%14,%15,%16,%17}, %18, 1, 1, 1, 0;"
                 : R4(d, 0), R4(d, 4), R4(d, 8), "+r"(d[12]), "+r"(d[13])
                 : "r"(a[0]), "r"(a[1]), "r"(a[2]), "r"(a[3]), "l"(db));
  else
    asm volatile("wgmma.mma_async.sync.aligned.m64n56k16.f16.f16.f16 " D14 "{%14,%15,%16,%17}, %18, 0, 1, 1, 0;"
                 : O4(d, 0), O4(d, 4), O4(d, 8), "=r"(d[12]), "=r"(d[13])
                 : "r"(a[0]), "r"(a[1]), "r"(a[2]), "r"(a[3]), "l"(db));
}
template <int SC>
__device__ __forceinline__ void gemm_w(uint32_t (&d)[24], const uint32_t* a, uint64_t dw, uint32_t acc = 0) {
  wg_fence();
  wg96h<SC, 0>(d, a, dw, acc); wg96h<1, 0>(d, a + 4, dw + 2);
  wg96h<1, 0>(d, a + 8, dw + 384); wg96h<1, 0>(d, a + 12, dw + 386);
  wg96h<1, 0>(d, a + 16, dw + 768); wg96h<1, 0>(d, a + 20, dw + 770);
  wg_commit();
}
__device__ __forceinline__ void lds128(uint32_t* r, uint32_t a) {
  asm volatile("ld.shared.v4.b32 {%0,%1,%2,%3}, [%4];" : "=r"(r[0]), "=r"(r[1]), "=r"(r[2]), "=r"(r[3]) : "r"(a) : "memory");
}
__device__ __forceinline__ uint32_t lds32(uint32_t a) {
  uint32_t r; asm volatile("ld.volatile.shared.b32 %0, [%1];" : "=r"(r) : "r"(a) : "memory"); return r;
}
__device__ __forceinline__ void sts32(uint32_t a, uint32_t v) { asm volatile("st.volatile.shared.b32 [%0], %1;" ::"r"(a), "r"(v) : "memory"); }
__device__ __forceinline__ void ldsm4(uint32_t* r, uint32_t a) {
  asm volatile("ldmatrix.sync.aligned.m8n8.x4.shared.b16 {%0,%1,%2,%3}, [%4];"
               : "=r"(r[0]), "=r"(r[1]), "=r"(r[2]), "=r"(r[3]) : "r"(a) : "memory");
}
__device__ __forceinline__ void stsm4(uint32_t a, const uint32_t* r) {
  asm volatile("stmatrix.sync.aligned.m8n8.x4.shared.b16 [%0], {%1,%2,%3,%4};" ::"r"(a), "r"(r[0]), "r"(r[1]), "r"(r[2]), "r"(r[3])
               : "memory");
}
__device__ __forceinline__ uint32_t pack_h2(float lo, float hi) {
  uint32_t r; asm("cvt.rn.f16x2.f32 %0, %1, %2;" : "=r"(r) : "f"(hi), "f"(lo)); return r;
}
__device__ __forceinline__ uint32_t pack_h2_sat(float lo, float hi) {
  uint32_t r; asm("cvt.rn.satfinite.f16x2.f32 %0, %1, %2;" : "=r"(r) : "f"(hi), "f"(lo)); return r;
}
__device__ __forceinline__ uint32_t pack_bf2(float lo, float hi) {
  uint32_t r; asm("cvt.rn.bf16x2.f32 %0, %1, %2;" : "=r"(r) : "f"(hi), "f"(lo)); return r;
}
__device__ __forceinline__ __half2 as_h2(uint32_t v) { return *reinterpret_cast<__half2*>(&v); }
__device__ __forceinline__ uint32_t as_u(__half2 v) { return *reinterpret_cast<uint32_t*>(&v); }
__device__ __forceinline__ float2 unpack_h2(uint32_t v) { return __half22float2(as_h2(v)); }
__device__ __forceinline__ uint32_t h2ex2(uint32_t v) { uint32_t r; asm("ex2.approx.f16x2 %0, %1;" : "=r"(r) : "r"(v)); return r; }
__device__ __forceinline__ uint32_t h2max(uint32_t a, uint32_t b) { return as_u(__hmax2(as_h2(a), as_h2(b))); }
__device__ __forceinline__ uint32_t h2add(uint32_t a, uint32_t b) { return as_u(__hadd2(as_h2(a), as_h2(b))); }
__device__ __forceinline__ uint32_t h2sub(uint32_t a, uint32_t b) { return as_u(__hsub2(as_h2(a), as_h2(b))); }
__device__ __forceinline__ uint32_t h2mul(uint32_t a, uint32_t b) { return as_u(__hmul2(as_h2(a), as_h2(b))); }
__device__ __forceinline__ uint32_t h2fma(uint32_t a, uint32_t b, uint32_t c) { return as_u(__hfma2(as_h2(a), as_h2(b), as_h2(c))); }
__device__ __forceinline__ uint32_t lo2(uint32_t v) { return as_u(__low2half2(as_h2(v))); }
__device__ __forceinline__ uint32_t hi2(uint32_t v) { return as_u(__high2half2(as_h2(v))); }
__device__ __forceinline__ uint32_t fold_add(uint32_t a, uint32_t b) { return h2add(__byte_perm(a, b, 0x5410), __byte_perm(a, b, 0x7632)); }
__device__ __forceinline__ uint32_t bitsel(uint32_t a, uint32_t m, uint32_t c) {
  uint32_t r; asm("lop3.b32 %0, %1, %2, %3, 0xe2;" : "=r"(r) : "r"(a), "r"(m), "r"(c)); return r;
}
__device__ __forceinline__ float rcp_fast(float v) { float r; asm("rcp.approx.ftz.f32 %0, %1;" : "=f"(r) : "f"(v)); return r; }
__device__ __forceinline__ float rsq_fast(float v) { float r; asm("rsqrt.approx.ftz.f32 %0, %1;" : "=f"(r) : "f"(v)); return r; }
__device__ __forceinline__ float quad_sum(float v) {
  v += __shfl_xor_sync(0xffffffffu, v, 1);
  return v + __shfl_xor_sync(0xffffffffu, v, 2);
}
__device__ __forceinline__ uint32_t quad_h2add(uint32_t v) {
  v = h2add(v, __shfl_xor_sync(0xffffffffu, v, 1));
  return h2add(v, __shfl_xor_sync(0xffffffffu, v, 2));
}
__device__ __forceinline__ uint32_t score_scale(const float* p) { const float v = __ldcg(p); return pack_h2(v, v); }

constexpr float kEps96 = 1e-5f * 96.f * 96.f;
__device__ __forceinline__ float2 stat_f32(uint32_t e) {
  const float2 h = unpack_h2(e);
  return make_float2((e & 0x8000u) ? __uint_as_float((e << 16) & 0x7fff0000u) : h.x, (e & 0x8000u) ? __uint_as_float(e & 0xffff0000u) : h.y);
}

__device__ __forceinline__ uint32_t swz(uint32_t a) { return a ^ ((a >> 3) & 0x30); }
__device__ __forceinline__ uint32_t prmt(uint32_t a, uint32_t b, uint32_t s) {
  uint32_t r; asm("prmt.b32 %0, %1, %2, %3;" : "=r"(r) : "r"(a), "r"(b), "r"(s)); return r;
}
__device__ __forceinline__ void tie48(uint32_t* a, uint32_t* b, uint64_t d, uint32_t u = 0, uint32_t v = 0) {
  asm volatile("{\n.reg .pred p;\n.reg .b32 t;\nsetp.ne.u32 p, %48, 0x7fffffff;\n@p bra.uni TIED;\n"
               "wgmma.fence.sync.aligned;\n"
               "wgmma.mma_async.sync.aligned.m64n192k16.f16.f16.f16 {%0,%1,%2,%3,%4,%5,%6,%7,%8,%9,%10,%11,%12,%13,%14,%15,%16,%17,%18,%19,%20,%21,%22,%23,%24,%25,%26,%27,%28,%29,%30,%31,%32,%33,%34,%35,%36,%37,%38,%39,%40,%41,%42,%43,%44,%45,%46,%47}, %49, %49, 1, 1, 1, 0, 0;\n"
               "wgmma.commit_group.sync.aligned;\nwgmma.wait_group.sync.aligned 0;\nTIED:\n}"
               : R4(a, 0), R4(a, 4), R4(a, 8), R4(a, 12), R4(a, 16), R4(a, 20), R4(b, 0), R4(b, 4), R4(b, 8), R4(b, 12), R4(b, 16), R4(b, 20)
               : "r"(gridDim.x), "l"(d), "r"(u), "r"(v) : "memory");
}
template <int N>
__device__ __forceinline__ void x_delay(uint32_t v) {
  if (N == 0) return;
  asm volatile("{\n.reg .pred p;\nsetp.eq.u32 p, %0, 0x7fffffff;\n"
#define XL1 "vote.sync.any.pred p, p, 0xffffffff;\n"
               XL1 XL1 XL1 XL1 XL1 XL1 XL1 XL1
               "@!p bra.uni XD;\nnanosleep.u32 %0;\nXD:\n}" ::"r"(v) : "memory");
}
template <int N>
__device__ __forceinline__ void x_work(uint32_t v) {
  if (N == 0) return;
  uint32_t a = v, b = v + 1, c = v + 2, d = v + 3;
#pragma unroll
  for (int i = 0; i < N / 4; i++)
    asm volatile("fma.rn.f16x2 %0, %0, %4, %4;\nfma.rn.f16x2 %1, %1, %4, %4;\nfma.rn.f16x2 %2, %2, %4, %4;\nfma.rn.f16x2 %3, %3, %4, %4;" : "+r"(a), "+r"(b), "+r"(c), "+r"(d) : "r"(v));
  sched_fence(a ^ b, c, d);
}
struct A3 { uint32_t a[3]; };
__device__ __forceinline__ A3 swz3(uint32_t a) { return A3{{swz(a), swz(a + kChunk), swz(a + 2 * kChunk)}}; }
__device__ __forceinline__ void load_row(uint32_t* x, const A3& a, int t) {
  lds128(x, a.a[0] + t * kFrame); lds128(x + 4, a.a[1] + t * kFrame); lds128(x + 8, a.a[2] + t * kFrame);
}
__device__ __forceinline__ void row_to_h2(uint32_t* y, const uint32_t* x) {
#pragma unroll
  for (int j = 0; j < 12; j += 2) {
    y[2 * j] = pack_h2(__uint_as_float(x[j] << 16), __uint_as_float(x[j + 1] << 16));
    uint32_t r;
    asm("cvt.rz.f16x2.f32 %0, %1, %2;" : "=r"(r) : "f"(__uint_as_float(x[j + 1])), "f"(__uint_as_float(x[j])));
    y[2 * j + 2] = r & 0xfff8fff8u;
  }
}
__device__ __forceinline__ void gemm_at(uint32_t (&q)[26], const uint32_t* z, uint64_t da) {
  wg_fence();
  wg104h<0>(q, z, da); wg104h<1>(q, z + 4, da + 2);
  wg104h<1>(q, z + 8, da + 416); wg104h<1>(q, z + 12, da + 418);
  wg104h<1>(q, z + 16, da + 832); wg104h<1>(q, z + 20, da + 834);
  wg_commit();
}
template <int SC>
__device__ __forceinline__ void wg64h(uint32_t* d, const uint32_t* a, uint64_t db) {
  if (SC)
    asm volatile("wgmma.mma_async.sync.aligned.m64n64k16.f16.f16.f16 {%0,%1,%2,%3,%4,%5,%6,%7,%8,%9,%10,%11,%12,%13,%14,%15}, {%16,%17,%18,%19}, %20, 1, 1, 1, 0;"
                 : "+r"(d[0]), "+r"(d[1]), "+r"(d[2]), "+r"(d[3]), "+r"(d[4]), "+r"(d[5]), "+r"(d[6]), "+r"(d[7]), "+r"(d[8]), "+r"(d[9]), "+r"(d[10]), "+r"(d[11]), "+r"(d[12]), "+r"(d[13]), "+r"(d[14]), "+r"(d[15])
                 : "r"(a[0]), "r"(a[1]), "r"(a[2]), "r"(a[3]), "l"(db));
  else
    asm volatile("wgmma.mma_async.sync.aligned.m64n64k16.f16.f16.f16 {%0,%1,%2,%3,%4,%5,%6,%7,%8,%9,%10,%11,%12,%13,%14,%15}, {%16,%17,%18,%19}, %20, 0, 1, 1, 0;"
                 : "=r"(d[0]), "=r"(d[1]), "=r"(d[2]), "=r"(d[3]), "=r"(d[4]), "=r"(d[5]), "=r"(d[6]), "=r"(d[7]), "=r"(d[8]), "=r"(d[9]), "=r"(d[10]), "=r"(d[11]), "=r"(d[12]), "=r"(d[13]), "=r"(d[14]), "=r"(d[15])
                 : "r"(a[0]), "r"(a[1]), "r"(a[2]), "r"(a[3]), "l"(db));
}
template <int SC>
__device__ __forceinline__ void wg40h(uint32_t* d, const uint32_t* a, uint64_t db) {
  if (SC)
    asm volatile("wgmma.mma_async.sync.aligned.m64n40k16.f16.f16.f16 {%0,%1,%2,%3,%4,%5,%6,%7,%8,%9}, {%10,%11,%12,%13}, %14, 1, 1, 1, 0;"
                 : "+r"(d[0]), "+r"(d[1]), "+r"(d[2]), "+r"(d[3]), "+r"(d[4]), "+r"(d[5]), "+r"(d[6]), "+r"(d[7]), "+r"(d[8]), "+r"(d[9])
                 : "r"(a[0]), "r"(a[1]), "r"(a[2]), "r"(a[3]), "l"(db));
  else
    asm volatile("wgmma.mma_async.sync.aligned.m64n40k16.f16.f16.f16 {%0,%1,%2,%3,%4,%5,%6,%7,%8,%9}, {%10,%11,%12,%13}, %14, 0, 1, 1, 0;"
                 : "=r"(d[0]), "=r"(d[1]), "=r"(d[2]), "=r"(d[3]), "=r"(d[4]), "=r"(d[5]), "=r"(d[6]), "=r"(d[7]), "=r"(d[8]), "=r"(d[9])
                 : "r"(a[0]), "r"(a[1]), "r"(a[2]), "r"(a[3]), "l"(db));
}
template <int SC>
__device__ __forceinline__ void wg80h(uint32_t* d, const uint32_t* a, uint64_t db) {
  if (SC)
    asm volatile("wgmma.mma_async.sync.aligned.m64n80k16.f16.f16.f16 {%0,%1,%2,%3,%4,%5,%6,%7,%8,%9,%10,%11,%12,%13,%14,%15,%16,%17,%18,%19}, {%20,%21,%22,%23}, %24, 1, 1, 1, 0;"
                 : "+r"(d[0]), "+r"(d[1]), "+r"(d[2]), "+r"(d[3]), "+r"(d[4]), "+r"(d[5]), "+r"(d[6]), "+r"(d[7]), "+r"(d[8]), "+r"(d[9]), "+r"(d[10]), "+r"(d[11]), "+r"(d[12]), "+r"(d[13]), "+r"(d[14]), "+r"(d[15]), "+r"(d[16]), "+r"(d[17]), "+r"(d[18]), "+r"(d[19])
                 : "r"(a[0]), "r"(a[1]), "r"(a[2]), "r"(a[3]), "l"(db));
  else
    asm volatile("wgmma.mma_async.sync.aligned.m64n80k16.f16.f16.f16 {%0,%1,%2,%3,%4,%5,%6,%7,%8,%9,%10,%11,%12,%13,%14,%15,%16,%17,%18,%19}, {%20,%21,%22,%23}, %24, 0, 1, 1, 0;"
                 : "=r"(d[0]), "=r"(d[1]), "=r"(d[2]), "=r"(d[3]), "=r"(d[4]), "=r"(d[5]), "=r"(d[6]), "=r"(d[7]), "=r"(d[8]), "=r"(d[9]), "=r"(d[10]), "=r"(d[11]), "=r"(d[12]), "=r"(d[13]), "=r"(d[14]), "=r"(d[15]), "=r"(d[16]), "=r"(d[17]), "=r"(d[18]), "=r"(d[19])
                 : "r"(a[0]), "r"(a[1]), "r"(a[2]), "r"(a[3]), "l"(db));
}
template <int SC>
__device__ __forceinline__ void wg24h(uint32_t* d, const uint32_t* a, uint64_t db) {
  if (SC)
    asm volatile("wgmma.mma_async.sync.aligned.m64n24k16.f16.f16.f16 {%0,%1,%2,%3,%4,%5}, {%6,%7,%8,%9}, %10, 1, 1, 1, 0;"
                 : "+r"(d[0]), "+r"(d[1]), "+r"(d[2]), "+r"(d[3]), "+r"(d[4]), "+r"(d[5])
                 : "r"(a[0]), "r"(a[1]), "r"(a[2]), "r"(a[3]), "l"(db));
  else
    asm volatile("wgmma.mma_async.sync.aligned.m64n24k16.f16.f16.f16 {%0,%1,%2,%3,%4,%5}, {%6,%7,%8,%9}, %10, 0, 1, 1, 0;"
                 : "=r"(d[0]), "=r"(d[1]), "=r"(d[2]), "=r"(d[3]), "=r"(d[4]), "=r"(d[5])
                 : "r"(a[0]), "r"(a[1]), "r"(a[2]), "r"(a[3]), "l"(db));
}
__device__ __forceinline__ void gemm_at2(uint32_t (&q)[26], const uint32_t* z, uint64_t da) {
  wg_fence();
#define WA wg64h
#define WB wg40h
  constexpr int o = SPN / 4, e = SPN * 4;
  WA<0>(q, z, da); WB<0>(q + o, z, da + e); WA<1>(q, z + 4, da + 2); WB<1>(q + o, z + 4, da + e + 2);
  WA<1>(q, z + 8, da + 416); WB<1>(q + o, z + 8, da + e + 416); WA<1>(q, z + 12, da + 418); WB<1>(q + o, z + 12, da + e + 418);
  WA<1>(q, z + 16, da + 832); WB<1>(q + o, z + 16, da + e + 832); WA<1>(q, z + 20, da + 834); WB<1>(q + o, z + 20, da + e + 834);
  wg_commit();
}
__device__ __forceinline__ void wg48h(uint32_t* d, const uint32_t* a, uint64_t db) {
  asm volatile("wgmma.mma_async.sync.aligned.m64n48k16.f16.f16.f16 {%0,%1,%2,%3,%4,%5,%6,%7,%8,%9,%10,%11}, {%12,%13,%14,%15}, %16, 1, 1, 1, 0;"
               : "+r"(d[0]), "+r"(d[1]), "+r"(d[2]), "+r"(d[3]), "+r"(d[4]), "+r"(d[5]), "+r"(d[6]), "+r"(d[7]), "+r"(d[8]), "+r"(d[9]), "+r"(d[10]), "+r"(d[11])
               : "r"(a[0]), "r"(a[1]), "r"(a[2]), "r"(a[3]), "l"(db));
}
__device__ __forceinline__ void gemm_w2(uint32_t* d, const uint32_t* a, uint64_t dw) {
  wg_fence();
#pragma unroll
  for (int k = 0; k < 6; k++) {
    wg48h(d, a + 4 * k, dw + (k >> 1) * 384 + (k & 1) * 2); wg48h(d + 12, a + 4 * k, dw + (k >> 1) * 384 + (k & 1) * 2 + 192);
  }
  wg_commit();
}
template <int kChains = 2>
__device__ __forceinline__ uint32_t sumsq(const uint32_t* z) {
  if (kChains == 1) {
    uint32_t a = h2mul(z[0], z[0]), b = h2mul(z[1], z[1]);
#pragma unroll
    for (int j = 1; j < 12; j++) { a = h2fma(z[2 * j], z[2 * j], a); b = h2fma(z[2 * j + 1], z[2 * j + 1], b); }
    return fold_add(a, b);
  }
  uint32_t q0[2], q1[2];
#pragma unroll
  for (int j = 0; j < 12; j++) {
    const uint32_t u = z[2 * j], v = z[2 * j + 1];
    q0[j & 1] = j < 2 ? h2mul(u, u) : h2fma(u, u, q0[j & 1]); q1[j & 1] = j < 2 ? h2mul(v, v) : h2fma(v, v, q1[j & 1]);
  }
  return fold_add(h2add(q0[0], q0[1]), h2add(q1[0], q1[1]));
}
__device__ __forceinline__ void scores_e(uint32_t* e, const uint32_t* q, const uint32_t* z) {
  uint32_t d[4];
#pragma unroll
  for (int j = 0; j < 12; j++) {
#pragma unroll
    for (int k = 0; k < 4; k++) d[k] = j ? h2fma(q[2 * j + (k >> 1)], z[2 * j + (k & 1)], d[k]) : h2mul(q[k >> 1], z[k & 1]);
  }
  e[0] = fold_add(d[0], d[2]); e[1] = fold_add(d[1], d[3]);
}
__device__ __forceinline__ uint32_t scores_r(const uint32_t* e, uint32_t selK) {
  return h2add(prmt(e[0], e[1], selK), __shfl_xor_sync(0xffffffffu, prmt(e[0], e[1], selK ^ 0x2222u), 1));
}
__device__ __forceinline__ uint32_t scores(const uint32_t* q, const uint32_t* z, uint32_t selK) {
  uint32_t e[2];
  scores_e(e, q, z);
  return scores_r(e, selK);
}
__device__ __forceinline__ float2 rstd(float2 d) { return make_float2(rsq_fast(fmaf(d.x, 1.f / 96.f, 1e-5f)), rsq_fast(fmaf(d.y, 1.f / 96.f, 1e-5f))); }
__device__ __forceinline__ void ln1_f32(uint32_t* z, const A3& la, int t, float* ie, float* m) {
  float acc[48];
  uint32_t x0[12], x1[12];
  load_row(x0, la, t); load_row(x1, la, t + 1);
#pragma unroll
  for (int j = 0; j < 12; j++) {
    acc[4 * j] = __uint_as_float(x0[j] << 16); acc[4 * j + 1] = __uint_as_float(x0[j] & 0xffff0000u);
    acc[4 * j + 2] = __uint_as_float(x1[j] << 16); acc[4 * j + 3] = __uint_as_float(x1[j] & 0xffff0000u);
  }
  float s[4], q[4];
#pragma unroll
  for (int e = 0; e < 4; e++) { s[e] = acc[e]; q[e] = acc[e] * acc[e]; }
#pragma unroll
  for (int j = 4; j < 48; j++) { s[j & 3] += acc[j]; q[j & 3] = fmaf(acc[j], acc[j], q[j & 3]); }
  const float s0 = quad_sum(s[0] + s[1]), s1 = quad_sum(s[2] + s[3]), q0 = quad_sum(q[0] + q[1]), q1 = quad_sum(q[2] + q[3]);
  const float u0 = rsq_fast(fmaxf(fmaf(-s0, s0, fmaf(q0, 96.f, kEps96)), kEps96));
  const float u1 = rsq_fast(fmaxf(fmaf(-s1, s1, fmaf(q1, 96.f, kEps96)), kEps96));
  const float n0 = -s0 * u0, n1 = -s1 * u1;
  ie[0] = 96.f * u0; ie[1] = 96.f * u1;
  m[0] = s0 * (1.f / 96.f); m[1] = s1 * (1.f / 96.f);
#pragma unroll
  for (int j = 0; j < 12; j++) {
    const int e = 4 * (j & ~1) + (j & 1);
    z[2 * j] = pack_h2(fmaf(acc[e], ie[0], n0), fmaf(acc[e + 4], ie[0], n0));
    z[2 * j + 1] = pack_h2(fmaf(acc[e + 2], ie[1], n1), fmaf(acc[e + 6], ie[1], n1));
  }
}
__device__ __forceinline__ float2 sumsq_f32(const uint32_t* z) {
  float2 qq = make_float2(0.f, 0.f);
#pragma unroll
  for (int j = 0; j < 12; j++) {
    const float2 u = unpack_h2(z[2 * j]), v = unpack_h2(z[2 * j + 1]);
    qq.x = fmaf(u.x, u.x, fmaf(u.y, u.y, qq.x)); qq.y = fmaf(v.x, v.x, fmaf(v.y, v.y, qq.y));
  }
  return make_float2(quad_sum(qq.x), quad_sum(qq.y));
}
__device__ __forceinline__ float2 var96_f32(const uint32_t* z, uint32_t my) {
  const float2 q = sumsq_f32(z), m = unpack_h2(my);
  return make_float2(fmaf(-96.f * m.x, m.x, q.x), fmaf(-96.f * m.y, m.y, q.y));
}
__device__ __forceinline__ void ln2(uint32_t* h, uint32_t rr, uint32_t my, const A3& ma, int t) {
  const uint32_t nn = as_u(__hmul2(__hneg2(as_h2(my)), as_h2(rr)));
#pragma unroll
  for (int j = 0; j < 12; j++) { h[2 * j] = h2fma(h[2 * j], lo2(rr), lo2(nn)); h[2 * j + 1] = h2fma(h[2 * j + 1], hi2(rr), hi2(nn)); }
#pragma unroll
  for (int k = 0; k < 3; k++) { stsm4(ma.a[k] + t * kFrame, h + 8 * k); stsm4((ma.a[k] ^ 32) + t * kFrame, h + 8 * k + 4); }
}

__device__ __forceinline__ uint32_t ring_pos(uint32_t r) { return min(r, r - 196u); }
__device__ __forceinline__ uint32_t ring_row(uint32_t r) { return ((r * 1338u) >> 16) * (kBufStride - kChunk) + r * 64; }
__device__ __forceinline__ uint32_t ring_stat(uint32_t r) { return ((r * 1338u) >> 16) * (kBufStride - 49 * 4) + r * 4; }
__device__ __forceinline__ A3 t_in_addr(uint32_t sb, uint32_t r0, int lane) {
  return swz3(sb + kOffBuf + (lane & 3) * 16 + ring_row(ring_pos(r0 + (lane >> 2))));
}
__device__ __forceinline__ A3 t_out_addr(uint32_t sb, uint32_t r0, int lane) {
  return swz3(sb + kOffBuf + ((lane >> 3) & 1) * kFrame + (lane & 16) + ring_row(ring_pos(r0 + (lane & 7))));
}
__device__ __forceinline__ uint32_t t_stat_addr(uint32_t sb, uint32_t r0, int lane) {
  return sb + kOffBuf + kXBytes + (lane & 3) * kFrame + ring_stat(ring_pos(r0 + (lane >> 2)));
}
__device__ __forceinline__ void t_release(uint32_t bar, uint32_t ia, uint32_t ib, int lane) {
  __syncwarp();
  asm volatile("{\n.reg .pred p;\nsetp.le.u32 p, %1, %2;\n@p mbarrier.arrive.shared::cta.b64 _, [%0];\n}"
               ::"r"(bar + ((ia + lane) & 3) * 8), "r"(lane), "r"(ib - ia) : "memory");
}
template <bool kDirect>
__device__ __forceinline__ void softmax4(uint32_t* s, uint32_t rhoA, uint32_t rhoB, uint32_t ro, float f) {
  if (kDirect) { s[0] = h2mul(s[0], rhoA); s[1] = h2mul(s[1], rhoB); }
  uint32_t mx = h2max(s[0], s[1]);
  mx = h2max(lo2(mx), hi2(mx));
  if (kDirect) {
    const uint32_t nm = as_u(__hmul2(__hneg2(as_h2(mx)), as_h2(ro)));
    s[0] = h2fma(s[0], ro, nm); s[1] = h2fma(s[1], ro, nm);
  } else {
    s[0] = h2mul(h2sub(s[0], mx), ro); s[1] = h2mul(h2sub(s[1], mx), ro);
  }
  s[0] = h2ex2(s[0]); s[1] = h2ex2(s[1]);
  uint32_t sm = h2add(s[0], s[1]);
  sm = h2add(lo2(sm), hi2(sm));
  const float iv = f * rcp_fast(__low2float(as_h2(sm)));
  const uint32_t inv = pack_h2(iv, iv);
  if (kDirect) { s[0] = h2mul(h2mul(s[0], rhoA), inv); s[1] = h2mul(h2mul(s[1], rhoB), inv); }
  else { s[0] = h2mul(s[0], inv); s[1] = h2mul(s[1], inv); }
}
template <bool kFirst>
__device__ __forceinline__ void mix(uint32_t* u, const uint32_t* z, uint32_t p0, uint32_t p1) {
#pragma unroll
  for (int j = 0; j < 12; j++) {
    u[2 * j] = h2fma(z[2 * j + 1], hi2(p0), kFirst ? h2mul(z[2 * j], lo2(p0)) : h2fma(z[2 * j], lo2(p0), u[2 * j]));
    u[2 * j + 1] = h2fma(z[2 * j + 1], hi2(p1), kFirst ? h2mul(z[2 * j], lo2(p1)) : h2fma(z[2 * j], lo2(p1), u[2 * j + 1]));
  }
}
template <bool kDirect>
__device__ __forceinline__ void put_stats(uint32_t sa, float sg, float mm, const Params& P) {
  const bool ok = (sg >= P.sgmin) & (kDirect || fmaf(sg, 9.8f, fabsf(mm)) < fmaf(P.kappa, -627.2f, 60000.f));
  const uint32_t sh = pack_h2(sg, mm), sw = pack_bf2(-sg, mm);
  asm volatile("st.shared.b32 [%0], %1;" ::"r"(sa), "r"(ok ? sh : sw) : "memory");
}

__device__ __forceinline__ bool task_T(uint32_t sb, uint32_t r0, uint32_t ia, uint32_t ib, uint32_t flag, int lane, const Params& P TRARG) {
  TR(1);
  const int c = lane & 3;
  const uint32_t selK = (c & 1) ? 0x7632u : 0x5410u, selO = 0x1010u + c * 0x2222u;
  const uint64_t da = mk_desc(sb, 1), dw = mk_desc(sb + kOffWt, 1);
  uint32_t x[48], yA[24], yB[24], qA[26], qB[26], ssA, ssB;
  {
    const A3 la = t_in_addr(sb, r0, lane);
#pragma unroll
    for (int t = 0; t < 4; t++) load_row(x + 12 * t, la, t);
  }
  row_to_h2(yA, x); row_to_h2(yA + 1, x + 12);
  TR(2);
  row_to_h2(yB, x + 24); row_to_h2(yB + 1, x + 36);
  ssB = sumsq<C1>(yB);
  ssA = sumsq<C1>(yA);
  if (SPL & 1) gemm_at2(qA, yA, da); else gemm_at(qA, yA, da);
  if (SPL & 2) gemm_at2(qB, yB, da); else gemm_at(qB, yB, da);
  TR(3);
  ssB = quad_h2add(ssB);
  ssA = quad_h2add(ssA);
  uint32_t rA[2], rB[2];
  wg_wait<1>(); pin<26>(qA);
  TR(4);
  const uint32_t myA = __byte_perm(qA[24], qA[25], 0x5410), nuA = __byte_perm(qA[24], qA[25], 0x7632);
  const uint32_t nsA = h2mul(myA, 0xd600d600u);
  const float2 ra = rstd(unpack_h2(h2fma(nsA, myA, ssA)));
  const uint32_t rhoA = pack_h2(ra.x, ra.y);
  rA[0] = scores(qA, yA, selK);
  sched_fence(rA[0], rhoA, 0);
  wg_wait<0>(); pin<26>(qB);
  TR(5);
  const uint32_t myB = __byte_perm(qB[24], qB[25], 0x5410), nuB = __byte_perm(qB[24], qB[25], 0x7632);
  const uint32_t nsB = h2mul(myB, 0xd600d600u);
  const float2 rb = rstd(unpack_h2(h2fma(nsB, myB, ssB)));
  const uint32_t rhoB = pack_h2(rb.x, rb.y);
  const uint32_t ro = prmt(rhoA, rhoB, selO), mo = bitsel(prmt(myA, myB, selO), 0xffffu, 0x292e0000u);
  asm volatile("{\n.reg .pred p, q;\n.reg .b32 t;\nabs.f16x2 t, %1;\nsetp.gtu.f16x2 p|q, t, %2;\nor.pred p, p, q;\n@p st.volatile.shared.b32 [%0], %2;\n}"
               ::"r"(flag), "r"(h2fma(ro, mo, 0xbc190000u)), "r"(0x3c003c00u) : "memory");
  uint32_t mu;
  rA[1] = scores(qA, yB, selK); rB[0] = scores(qB, yA, selK); rB[1] = scores(qB, yB, selK);
  uint32_t p[8], s[2];
#pragma unroll
  for (int k = 0; k < 2; k++) s[k] = h2add((c & 2) ? rB[k] : rA[k], __shfl_xor_sync(0xffffffffu, (c & 2) ? rA[k] : rB[k], 2));
  softmax4<true>(s, rhoA, rhoB, ro, P.kt);
#pragma unroll
  for (int t = 0; t < 4; t++) { p[2 * t] = __shfl_sync(0xffffffffu, s[0], t, 4); p[2 * t + 1] = __shfl_sync(0xffffffffu, s[1], t, 4); }
  mu = h2fma(s[1], nuB, h2mul(s[0], nuA));
  mix<true>(qA, yA, p[0], p[2]); mix<false>(qA, yB, p[1], p[3]);
  mu = h2add(lo2(mu), hi2(mu));
  mix<true>(qB, yA, p[4], p[6]);
  TR(6);
  if (SPL & 4) gemm_w2(yA, qA, dw); else gemm_w<1>(yA, qA, dw);
  sched_fence(0, 0, 0);
  mix<false>(qB, yB, p[5], p[7]);
  if (SPL & 8) gemm_w2(yB, qB, dw); else gemm_w<1>(yB, qB, dw);
  const A3 ma = t_out_addr(sb, r0, lane);
  TR(7);
  wg_wait<1>(); pin<24>(yA);
  TR(8);
  uint32_t bad;
  asm volatile("ld.shared.b32 %0, [%1];" : "=r"(bad) : "r"(flag + (yA[0] & (gridDim.x == 0x7fffffffu))) : "memory");
  float2 d = unpack_h2(h2fma(nsA, myA, quad_h2add(sumsq<C2>(yA))));
  if (UNLIKELY(__any_sync(0xffffffffu, !(d.x + d.y < 65000.f) | (bad != 0)))) {
    if (__any_sync(0xffffffffu, bad != 0)) {
      wg_wait<0>(); pin<24>(yB);
      return false;
    }
    d = var96_f32(yA, myA);
  }
  float2 r = rstd(make_float2(fabsf(d.x), fabsf(d.y)));
  const uint32_t rrA = pack_h2(r.x, r.y);
  ln2(yA, rrA, myA, ma, 0);
  if (DA) t_release(sb + kOffBar + 32, ia, ib, lane);
  wg_wait<0>(); pin<24>(yB);
  TR(9);
  d = unpack_h2(h2fma(nsB, myB, quad_h2add(sumsq<C2>(yB))));
  if (UNLIKELY(__any_sync(0xffffffffu, !(d.x + d.y < 65000.f)))) d = var96_f32(yB, myB);
  r = rstd(make_float2(fabsf(d.x), fabsf(d.y)));
  const uint32_t rrB = pack_h2(r.x, r.y);
  ln2(yB, rrB, myB, ma, 2);
  put_stats<true>(t_stat_addr(sb, r0, lane), rcp_fast(__low2float(as_h2(prmt(rrA, rrB, selO)))), __low2float(as_h2(h2add(mo, mu))), P);
  return true;
}

__device__ __forceinline__ void task_T_general(uint32_t sb, uint32_t r0, const Params& P) {
  int lane;
  asm volatile("mov.u32 %0, %%laneid;" : "=r"(lane));
  const int c = lane & 3;
  const uint64_t da = mk_desc(sb, 1), dw = mk_desc(sb + kOffWt, 1);
  uint32_t yA[24], yB[24], qA[26], qB[26];
  float ieo, mo, ao;
  {
    float ie[4], m[4];
    const A3 la = t_in_addr(sb, r0, lane);
    ln1_f32(yA, la, 0, ie, m);
    ln1_f32(yB, la, 2, ie + 2, m + 2);
    const float2 na = sumsq_f32(yA), nb = sumsq_f32(yB);
    const float ik = 9.8f * rcp_fast(P.kt) * rsq_fast(fmaxf(fmaxf(fmaxf(na.x, na.y), fmaxf(nb.x, nb.y)), 2e-7f));
    ieo = (c & 2) ? ((c & 1) ? ie[3] : ie[2]) : ((c & 1) ? ie[1] : ie[0]);
    mo = (c & 2) ? ((c & 1) ? m[3] : m[2]) : ((c & 1) ? m[1] : m[0]);
    const bool lim = (ieo * P.kt > 400.f) & (ik < ieo);
    const float u = ik * rcp_fast(ieo);
    ao = lim ? u : 1.f; ieo = lim ? ik : ieo;
  }
  uint32_t rA[2], rB[2], s[2], p[8];
  const uint32_t selK = (c & 1) ? 0x7632u : 0x5410u;
  gemm_at(qA, yA, da);
  wg_wait<0>(); pin<26>(qA);
  const uint32_t nuA = __byte_perm(qA[24], qA[25], 0x7632);
  rA[0] = scores(qA, yA, selK); rA[1] = scores(qA, yB, selK);
  sched_fence(rA[0], rA[1], nuA);
  gemm_at(qB, yB, da);
  wg_wait<0>(); pin<26>(qB);
  const uint32_t nuB = __byte_perm(qB[24], qB[25], 0x7632);
  rB[0] = scores(qB, yA, selK); rB[1] = scores(qB, yB, selK);
#pragma unroll
  for (int k = 0; k < 2; k++) s[k] = h2add((c & 2) ? rB[k] : rA[k], __shfl_xor_sync(0xffffffffu, (c & 2) ? rA[k] : rB[k], 2));
  softmax4<false>(s, 0, 0, score_scale(&g_par.cS_t), P.kt * ieo);
  uint32_t mu = h2fma(s[1], nuB, h2mul(s[0], nuA));
  mu = h2add(lo2(mu), hi2(mu));
#pragma unroll
  for (int t = 0; t < 4; t++) { p[2 * t] = __shfl_sync(0xffffffffu, s[0], t, 4); p[2 * t + 1] = __shfl_sync(0xffffffffu, s[1], t, 4); }
  sched_fence(mu, 0, 0);
  mix<true>(qA, yA, p[0], p[2]); mix<false>(qA, yB, p[1], p[3]);
  mix<true>(qB, yA, p[4], p[6]); mix<false>(qB, yB, p[5], p[7]);
  const uint32_t ah = pack_h2(ao, ao);
#pragma unroll
  for (int t = 0; t < 4; t++) {
    const uint32_t a = __shfl_sync(0xffffffffu, ah, t, 4);
#pragma unroll
    for (int j = 0; j < 12; j++) asm volatile("mul.f16x2 %0, %0, %1;" : "+r"(((t & 2) ? yB : yA)[2 * j + (t & 1)]) : "r"(a));
  }
  gemm_w<1>(yA, qA, dw);
  gemm_w<1>(yB, qB, dw);
  wg_wait<0>(); pin<24>(yA); pin<24>(yB);
  asm volatile("mov.u32 %0, %%laneid;" : "=r"(lane));
  float ie[4];
#pragma unroll
  for (int t = 0; t < 4; t++) ie[t] = __shfl_sync(0xffffffffu, ieo, t, 4);
  const float2 da2 = sumsq_f32(yA), db2 = sumsq_f32(yB);
  const uint32_t rrA = pack_h2_sat(rsq_fast(fmaf(da2.x, 1.f / 96.f, 1e-5f * ie[0] * ie[0])), rsq_fast(fmaf(da2.y, 1.f / 96.f, 1e-5f * ie[1] * ie[1])));
  const uint32_t rrB = pack_h2_sat(rsq_fast(fmaf(db2.x, 1.f / 96.f, 1e-5f * ie[2] * ie[2])), rsq_fast(fmaf(db2.y, 1.f / 96.f, 1e-5f * ie[3] * ie[3])));
  const A3 ma = t_out_addr(sb, r0, lane);
  ln2(yA, rrA, 0u, ma, 0); ln2(yB, rrB, 0u, ma, 2);
  const float r = __low2float(as_h2(prmt(rrA, rrB, 0x1010u + (lane & 3) * 0x2222u))), sg = rcp_fast(r * ieo);
  put_stats<false>(t_stat_addr(sb, r0, lane), sg, fmaf(__low2float(as_h2(mu)) * r, sg, mo), P);
}

__device__ __forceinline__ void loop_T(uint32_t sb, int nw, int wg, int wp, int lane, const Params& P, bool direct TRARG) {
  const uint32_t barF = sb + kOffBar, barD = sb + (DA ? kOffBarB : kOffBar + 32), flag = sb + kOffFlag + wg * 4;
  mbar_wait(sb + kOffBarW, 0);
  uint32_t r0 = 32 * wg + 8 * wp, par = 0;
  for (int k = (49 * nw + 63 - 32 * wg) >> 6; k > 0; k--) {
    TR(0);
    const uint32_t ia = (r0 * 1338u) >> 16, ib = ((r0 + 7) * 1338u) >> 16;
    mbar_wait(barF + ia * 8, par);
    if (UNLIKELY(ib != ia)) mbar_wait(barF + (ib & 3) * 8, par ^ (ib >> 2));
    const uint32_t r = r0;
    r0 += 64;
    if (r0 >= 196) { r0 -= 196; par ^= 1; }
    if (LIKELY(direct)) {
      if (LIKELY(task_T(sb, r, ia, ib, flag, lane, P TRPASS(trp)))) {
        t_release(barD, ia, ib, lane);
        continue;
      }
      asm volatile("barrier.cta.sync.aligned %0, 128;" ::"r"(wg + 1) : "memory");
      asm volatile("st.shared.b32 [%0], %1;\nfence.acq_rel.cta;" ::"r"(flag), "r"(0) : "memory");
    }
    task_T_general(sb, r, P);
    if (DA) t_release(sb + kOffBar + 32, ia, ib, lane);
    t_release(barD, ia, ib, lane);
  }
}

struct SFrame {
  uint32_t oo;
  uint32_t t, tg;
  uint32_t st;
  bool light;
};
__device__ __forceinline__ SFrame s_frame(int t, int tg, int wp, int lane, A3& ma) {
  SFrame f;
  const int rb = (wp + t) & 3;
  f.light = rb == 3;
  f.t = t; f.tg = tg;
  f.st = t * kFrame + kXBytes + rb * 64;
  ma = swz3(t * kFrame + rb * 1024 + ((lane * 65) & 0x3d0));
  if (f.light && (lane & 15)) ma.a[0] = ma.a[1] = ma.a[2] = kXBytes + 256;
  const uint32_t r = 16 * rb + (lane >> 2);
  f.oo = (r + (r / 7) * (kW - 7)) * 12 + (lane & 3) + (((r + 8 + ((r + 8) / 7) * (kW - 7)) * 12 + (lane & 3)) << 16);
  asm volatile("" : "+r"(f.oo));
  return f;
}
template <int kRow>
__device__ __forceinline__ uint8_t* out_row(uint8_t* ob, const SFrame& f) {
  uint32_t o = f.oo;
  asm volatile("" : "+r"(o));
  return ob + (uint64_t)(kRow ? o >> 16 : o & 0xffffu) * 16;
}
template <int kHi>
__device__ __forceinline__ void s_load(uint32_t (&v)[24], uint32_t buf, A3 ma) {
  asm volatile("" : "+r"(ma.a[0]), "+r"(ma.a[1]), "+r"(ma.a[2]));
#pragma unroll
  for (int k = 0; k < 3; k++) {
    const uint32_t a = kHi ? ma.a[k] >> 16 : ma.a[k] & 0xffffu;
    ldsm4(v + 8 * k, buf + a); ldsm4(v + 8 * k + 4, buf + (a ^ 32));
  }
}
__device__ __forceinline__ void gemm_s(uint32_t* s, const uint32_t* q, uint32_t pl) {
  const uint64_t dA = mk_desc(pl, 1);
  wg_fence();
  wg56h<0>(s, q, dA); wg56h<1>(s, q + 4, dA + 2);
  wg56h<1>(s, q + 8, dA + 196); wg56h<1>(s, q + 12, dA + 198);
  wg56h<1>(s, q + 16, dA + 392); wg56h<1>(s, q + 20, dA + 394);
  wg_commit();
}
template <bool kAll>
__device__ __forceinline__ void stg128(uint8_t* o, const uint32_t* w, uint32_t doit) {
  if (kAll) asm volatile("st.global.v4.b32 [%0], {%1,%2,%3,%4};" ::"l"(o), "r"(w[0]), "r"(w[1]), "r"(w[2]), "r"(w[3]) : "memory");
  else asm volatile("{\n.reg .pred p;\nsetp.ne.u32 p, %5, 0;\n@p st.global.v4.b32 [%0], {%1,%2,%3,%4};\n}" ::"l"(o), "r"(w[0]), "r"(w[1]), "r"(w[2]), "r"(w[3]), "r"(doit) : "memory");
}
template <int kRow, bool kAll>
__device__ __forceinline__ void s_store(const uint32_t (&v)[24], uint32_t e, uint8_t* o) {
  uint32_t w[12];
#pragma unroll
  for (int j = 0; j < 12; j += 2) {
    const float2 y = unpack_h2(h2fma(v[2 * j + kRow], lo2(e), hi2(e))), z = unpack_h2(h2fma(v[2 * j + 2 + kRow], lo2(e), hi2(e)));
    w[j] = pack_bf2(y.x, z.x); w[j + 1] = pack_bf2(y.y, z.y);
  }
#pragma unroll
  for (int i3 = 0; i3 < 3; i3++) stg128<kAll>(o + 64 * i3, w + 4 * i3, e);
}
template <int kRow, bool kAdd>
__device__ __forceinline__ void s_store_wide(const uint32_t (&v)[24], uint32_t e, uint8_t* o, const Params& P) {
  const float2 z = stat_f32(e);
#pragma unroll
  for (int i3 = 0; i3 < 3; i3++) {
    uint32_t w[4] = {0, 0, 0, 0};
    if (kAdd)
      asm volatile("{\n.reg .pred p;\nsetp.ne.u32 p, %5, 0;\n@p ld.global.v4.b32 {%0,%1,%2,%3}, [%4];\n}"
                   : "+r"(w[0]), "+r"(w[1]), "+r"(w[2]), "+r"(w[3]) : "l"(o + 64 * i3), "r"(e) : "memory");
#pragma unroll
    for (int j = 0; j < 4; j++) {
      const float2 ya = unpack_h2(v[8 * i3 + 2 * (j & 2) + kRow]), yb = unpack_h2(v[8 * i3 + 2 * (j & 2) + 2 + kRow]);
      const float2 y = (j & 1) ? make_float2(ya.y, yb.y) : make_float2(ya.x, yb.x);
      w[j] = kAdd ? pack_bf2(fmaf(y.x, P.kappa, __uint_as_float(w[j] << 16)), fmaf(y.y, P.kappa, __uint_as_float(w[j] & 0xffff0000u)))
                  : pack_bf2(fmaf(y.x, z.x, z.y), fmaf(y.y, z.x, z.y));
    }
    stg128<false>(o + 64 * i3, w, e);
  }
  __syncwarp();
}
__device__ __forceinline__ uint32_t ex2_pair(uint32_t s, uint32_t sel) {
  uint32_t lo, hi;
  asm volatile("{\n.reg .b16 a, b, c;\nmov.b32 {a, b}, %2;\nex2.approx.f16 c, a;\ncvt.u32.u16 %0, c;\nex2.approx.f16 c, b;\ncvt.u32.u16 %1, c;\n}"
               : "=r"(lo), "=r"(hi) : "r"(s));
  return QP ? prmt(lo, hi, sel) : lo + hi * 65536u;
}
__device__ __forceinline__ uint32_t ex2_lo(uint32_t s) {
  uint32_t lo;
  asm volatile("{\n.reg .b16 a, b, c;\nmov.b32 {a, b}, %1;\nex2.approx.f16 c, a;\ncvt.u32.u16 %0, c;\n}" : "=r"(lo) : "r"(s));
  return lo;
}

__device__ __forceinline__ void turn_wait(uint32_t j) { asm volatile("barrier.cta.sync.aligned %0, 256;" ::"r"(3 + j) : "memory"); }
__device__ __forceinline__ void turn_pass(uint32_t j) { asm volatile("barrier.cta.arrive.aligned %0, 256;" ::"r"(4 - j) : "memory"); }

template <int kSecond>
__device__ __forceinline__ void step_S(uint32_t sb, uint32_t (&v)[24], uint32_t (&vn)[24], uint32_t (&q)[24], uint32_t (&s)[16], const SFrame& f,
                                       const SFrame& fn, const A3& ma, uint32_t i, int nw, uint32_t w, uint32_t wlast, uint8_t* ob, int lane, const Params& P,
                                       bool scaled, const CUtensorMap* tm TRARG) {
  TR(0);
  const uint32_t ia = i & 3, ib = kSecond ? (i + 1) & 3 : ia;
  const uint32_t buf = sb + kOffBuf + ia * kBufStride, bufn = sb + kOffBuf + ib * kBufStride;
  const uint32_t never = gridDim.x == 0x7fffffffu;
  const uint64_t dQ0 = mk_desc(sb + kOffAs, 1), dQ = (HQ & 1) ? dQ0 : dQ0 + ((i + kSecond) & never), dW = ((HQ & 2) ? dQ0 : dQ0 + ((i + kSecond) & never)) + (kWMat >> 4);
  uint32_t p[16], u[24], e0, e1;
  ob += f.tg * (kH * kW * 192u);
  asm volatile("" : "+l"(ob));
  uint32_t g4 = lane;
  asm volatile("" : "+r"(g4));
  uint32_t stu = buf + f.st;
  asm volatile("" : "+r"(stu));
  const uint32_t sta = stu + (g4 & 0x1c);
  asm volatile("ld.shared.b32 %0, [%1];" : "=r"(e0) : "r"(sta) : "memory");
  asm volatile("ld.shared.b32 %0, [%1];" : "=r"(e1) : "r"(sta + 32) : "memory");
  const uint32_t keep = (lane & 3) == 0 ? 0x0000ffffu : 0u;
  const bool pad0 = QP && f.light && lane >= 4, pad1 = QP && f.light;
  const uint32_t sel0 = pad0 ? 0x3232u : 0x5410u, sel1 = pad1 ? 0x3232u : 0x5410u;
  s[12] = bitsel(s[12], QP == 1 && pad0 ? 0u : keep, 0xfc00fc00u); s[13] = bitsel(s[13], QP == 1 && pad1 ? 0u : keep, 0xfc00fc00u);
  const uint32_t x0 = h2max(h2max(h2max(h2max(s[0], s[2]), s[4]), h2max(h2max(s[6], s[8]), s[10])), s[12]);
  const uint32_t x1 = h2max(h2max(h2max(h2max(s[1], s[3]), s[5]), h2max(h2max(s[7], s[9]), s[11])), s[13]);
  const bool ok = __hble2(__hmax2(__habs2(as_h2(x0)), __habs2(as_h2(x1))), as_h2(0x47004700u)) & !scaled;
  constexpr int kE = IL == 0 ? 12 : IL == 1 ? 4 : IL == 2 ? 0 : 8;
  p[12] = ex2_lo(s[12]); p[13] = ex2_lo(s[13]);
#pragma unroll
  for (int j = 0; j < kE; j++) p[j] = ex2_pair(s[j], (j & 1) ? sel1 : sel0);
  if (UNLIKELY(!__all_sync(0xffffffffu, ok))) {
    uint32_t mx = h2max(__byte_perm(x0, x1, 0x5410), __byte_perm(x0, x1, 0x7632));
    mx = h2max(mx, __shfl_xor_sync(0xffffffffu, mx, 1));
    mx = h2max(mx, __shfl_xor_sync(0xffffffffu, mx, 2));
    const uint32_t cs = lds32(sb + kOffFlag + 8);
#pragma unroll
    for (int j = 0; j < 7; j++) { s[2 * j] = h2mul(h2sub(s[2 * j], lo2(mx)), cs); s[2 * j + 1] = h2mul(h2sub(s[2 * j + 1], hi2(mx)), cs); }
    p[12] = ex2_lo(s[12]); p[13] = ex2_lo(s[13]);
#pragma unroll
    for (int j = 0; j < kE; j++) p[j] = ex2_pair(s[j], (j & 1) ? sel1 : sel0);
  }
  asm volatile("mov.b32 %0, 0;\nmov.b32 %1, 0;" : "=r"(p[14]), "=r"(p[15]));
  TR(1);
  const uint64_t mn = mk_desc(buf + f.t * kFrame, kChunk >> 4);
  wg_fence();
  wg96h<2, 1>(q, p + 12, mn + 192, never); wg96h<1, 1>(q, p, mn);
#pragma unroll
  for (int j = 4; j < 12; j++) p[j] = ex2_pair(s[j], (j & 1) ? sel1 : sel0);
  const bool wide = __any_sync(0xffffffffu, ((e0 | e1) & 0x8000u) != 0u);
  uint32_t rs = fold_add(h2add(h2add(h2add(p[0], p[2]), p[12]), h2add(h2add(p[4], p[6]), h2add(p[8], p[10]))),
                         h2add(h2add(h2add(p[1], p[3]), p[13]), h2add(h2add(p[5], p[7]), h2add(p[9], p[11])))), rt;
  asm volatile("shfl.sync.bfly.b32 %0, %1, 1, 31, 0xffffffff;" : "=r"(rt) : "r"(rs));
  wg_fence();
  wg96h<1, 1>(q, p + 4, mn + 64); wg96h<1, 1>(q, p + 8, mn + 128);
  wg_commit();
  TR(2);
  if (UNLIKELY(wide)) { s_store_wide<0, false>(v, e0, out_row<0>(ob, f), P); s_store_wide<1, false>(v, e1, out_row<1>(ob, f), P); }
  rs = h2add(rs, rt);
  asm volatile("shfl.sync.bfly.b32 %0, %1, 2, 31, 0xffffffff;" : "=r"(rt) : "r"(rs));
  auto next = [&]() {
    if (i + 1 < nw) mbar_wait(sb + kOffBar + 32 + ib * 8, ((i + 1) >> 2) & 1);
    s_load<0>(vn, bufn, ma);
  };
  if (!kSecond) s_load<1>(vn, bufn, ma);
  else if (LD == 1) next();
  else if (LD == 3) s_load<0>(vn, bufn, ma);
  rs = h2add(rs, rt);
  const float d0 = __low2float(as_h2(rs)), d1 = __high2float(as_h2(rs));
  const float g0 = wide ? P.kappa : __low2float(as_h2(e0)), g1 = wide ? P.kappa : __low2float(as_h2(e1));
  const float c0 = P.kappa * rcp_fast(d0 * g0), c1 = P.kappa * rcp_fast(d1 * g1);
  uint32_t cb = QP == 1 ? pack_h2_sat(c0, c1) : pack_h2(e0 ? c0 : 0.f, e1 ? c1 : 0.f);
  if (PG == 1) turn_wait(f.t & 1);
  wg_wait<0>(); pin<24>(q);
  TR(3);
  if (PG == 2) turn_wait(f.t & 1);

  if (kSecond && LD == 2) next();
  auto refill = [&]() {
    if (f.light) {
      const uint32_t bar = sb + kOffBar + ia * 8;
      if (lane == 0) {
        if (i + 4 <= nw) tma_load(buf + f.t * kFrame, tm, bar, i + 5 >= nw ? wlast : w + 4 * gridDim.x, f.tg);
        if (!kSecond && (PF >= 2 || (f.t & 1) == PF0) && i + 4 <= nw) tma_prefetch(tm, i + 5 >= nw ? wlast : w + 4 * gridDim.x, fn.tg);
        if (kSecond && (PF == 4 || (PF == 3 && (f.t & 1) == PF0)) && i + 5 < nw) tma_prefetch(tm, i + 6 >= nw ? wlast : w + 5 * gridDim.x, fn.tg);
      }
      __syncwarp();
    }
  };
#pragma unroll
  for (int j = 0; j < 12; j++) { u[2 * j] = h2mul(q[2 * j], lo2(cb)); u[2 * j + 1] = h2mul(q[2 * j + 1], hi2(cb)); }
  if (PG == 3) turn_wait(f.t & 1);
  TR(4);
  gemm_w<2>(v, u, dW, !wide);
  if (PG && PR == 0) turn_pass(f.t & 1);

  if (RF == 0 || (RF == 1 && kSecond)) refill();
  if (kSecond && LD == 0) next();
  gemm_w<2>(q, vn, dQ, never);
  if (RF == 2 || (RF == 1 && !kSecond)) refill();
  if (PG && PR == 1) turn_pass(f.t & 1);
  TR(5);
  const bool plain = !(wide | f.light);
  wg_wait<1>(); pin<24>(v);
  if (kSecond || DA) asm volatile("fence.proxy.async.shared::cta;" ::: "memory");
  if (PG && PR == 2) turn_pass(f.t & 1);
  TR(6);
  if (LIKELY(plain)) s_store<0, true>(v, e0, out_row<0>(ob, f));
  if (PG && PR == 3) turn_pass(f.t & 1);
  wg_wait<0>(); pin<24>(q);
  TR(7);
  gemm_s(s, q, bufn + fn.t * kFrame);
  if (PG && PR == 4) turn_pass(f.t & 1);

  if (LIKELY(plain)) s_store<1, true>(v, e1, out_row<1>(ob, f));
  else if (!wide) { s_store<0, false>(v, e0, out_row<0>(ob, f)); __syncwarp(); }
  else if (wide) { s_store_wide<0, true>(v, e0, out_row<0>(ob, f), P); s_store_wide<1, true>(v, e1, out_row<1>(ob, f), P); }
  if (PG && PR == 5) turn_pass(f.t & 1);
  if (DA && kSecond && i + 1 < nw) mbar_wait(sb + kOffBarB + ib * 8, ((i + 1) >> 2) & 1);
  if (!kSecond && LD == 3 && i + 1 < nw) mbar_wait(sb + kOffBar + 32 + ((i + 1) & 3) * 8, ((i + 1) >> 2) & 1);
  wg_wait<0>(); pin<14>(s);
}

__device__ __forceinline__ void loop_S(uint32_t sb, int nw, bool half, uint32_t wlast, int t0, int tshift, int wp, int lane, const Params& P, bool scaled,
                                       const CUtensorMap* tm, uint8_t* __restrict__ out TRARG) {
  A3 ma, mb;
  const SFrame f0 = s_frame(t0, t0 ^ tshift, wp, lane, ma), f1 = s_frame(t0 + 2, (t0 + 2) ^ tshift, wp, lane, mb);
#pragma unroll
  for (int k = 0; k < 3; k++) ma.a[k] += mb.a[k] << 16;
  uint32_t v0[24], v1[24], q[24], s[16];
  sts32(sb + kOffFlag + 8, pack_h2(P.cS_s, P.cS_s));
  mbar_wait(sb + kOffBarW + 8, 0);
  mbar_wait(sb + kOffBar + 32, 0);
  s_load<0>(v0, sb + kOffBuf, ma);
  gemm_w<0>(q, v0, mk_desc(sb + kOffAs, 1));
  asm volatile("fence.proxy.async.shared::cta;" ::: "memory");
  wg_wait<0>(); pin<24>(q);
  gemm_s(s, q, sb + kOffBuf + f0.t * kFrame);
  if (DA) mbar_wait(sb + kOffBarB, 0);
  wg_wait<0>(); pin<14>(s);
  if (PG && t0 == PF0) turn_pass(t0);
  uint32_t w = blockIdx.x;
  for (uint32_t i = 0; i < nw; i++, w += gridDim.x) {
    if (i + 1 == nw) w = wlast;
    const uint32_t wy = (w * 57457u) >> 22;
    uint8_t* ob = out + (size_t)((wy * (7 * kW - 7 * kNWX) + w * 7) * 192u);
    asm volatile("" : "+l"(ob));
    step_S<0>(sb, v0, v1, q, s, f0, f1, ma, i, nw, w, wlast, ob, lane, P, scaled, tm TRPASS(trp + 16 * i));
    if (half && i + 1 == nw) break;
    step_S<1>(sb, v1, v0, q, s, f1, f0, ma, i, nw, w, wlast, ob, lane, P, scaled, tm TRPASS(trp + 16 * i + 8));
  }
  if (PG && t0 != PF0) turn_wait(t0);
  mbar_wait(sb + kOffBar + (nw & 3) * 8, (nw >> 2) & 1);
}

__global__ void __launch_bounds__(LB, 1) swin_main(const __grid_constant__ Maps maps, uint8_t* __restrict__ out) {
  const CUtensorMap& tm = maps.tm;
  extern __shared__ __align__(1024) uint8_t smem[];
  const uint32_t sb = smem_u32(smem);
  const int tid = threadIdx.x;
  const int wg = __shfl_sync(0xffffffffu, tid >> 7, 0);
  const int wp = __shfl_sync(0xffffffffu, (tid >> 5) & 3, 0);
  const int lane = tid & 31;
  const int b = blockIdx.x, nb = gridDim.x;
  const int nfull = kNWIN / nb, nrem = kNWIN - nfull * nb;
  const bool share = 2 * nrem <= nb;
  const int nw = nfull + (b < (share ? 2 * nrem : nrem));
  const bool half = share && nw > nfull;
  const uint32_t wlast = half && b >= nrem ? b - nrem + nfull * nb : b + (nw - 1) * nb;
  const uint32_t tshift = half && b >= nrem ? 2 : 0;
  if (tid == 0) {
    if ((sb & 1023) || nw < 5) __trap();
#pragma unroll
    for (int i = 0; i < 4; i++) {
      mbar_init(sb + kOffBar + i * 8, 4);
      mbar_init(sb + kOffBar + 32 + i * 8, 7);
      mbar_init(sb + kOffBarB + i * 8, 7);
    }
    asm volatile("st.shared.v2.b32 [%0], {%1,%1};" ::"r"(sb + kOffFlag), "r"(0) : "memory");
    mbar_init(sb + kOffBarW, 1); mbar_init(sb + kOffBarW + 8, 1);
    asm volatile("fence.mbarrier_init.release.cluster;" ::: "memory");
  }
  if (tid >= 128 && tid < 488) {
    const uint32_t e = tid - 128, fr = min(e / 20, 15u);
    asm volatile("st.shared.v4.b32 [%0], {%1,%1,%1,%1};" ::"r"(sb + kOffBuf + fr * kFrame + kXBytes + (e - fr * 20) * 16), "r"(0) : "memory");
    asm volatile("fence.proxy.async.shared::cta;" ::: "memory");
  }
#pragma unroll
  for (int i = 0; i < PAD; i++) sched_fence(tid + i, 0, 0);
  __syncthreads();
  if (lane == 0 && wg < 2) tma_load(sb + kOffBuf + (tid >> 5) * kFrame, &tm, sb + kOffBar + wg * 8, b + wg * nb, wp ^ tshift);
  __syncwarp();
  asm volatile("griddepcontrol.wait;" ::: "memory");
  if (tid == 0) {
    asm volatile("fence.proxy.async.global;" ::: "memory");
#pragma unroll
    for (int i = 0; i < 2; i++) {
      const uint32_t o = i ? kOffAs : 0, n = i ? kWBytes - kOffAs : kOffAs, bar = sb + kOffBarW + 8 * i;
      mbar_expect(bar, n);
      asm volatile("cp.async.bulk.shared::cluster.global.mbarrier::complete_tx::bytes [%0], [%1], %2, [%3];"
                   ::"r"(sb + o), "l"(reinterpret_cast<const uint8_t*>(g_wimg) + o), "r"(n), "r"(bar) : "memory");
    }
  }
  __syncwarp();
  if (wg >= 2) {
    if (WS) mbar_wait(sb + kOffBarW, 0);
    if (lane == 0) tma_load(sb + kOffBuf + (tid >> 5) * kFrame, &tm, sb + kOffBar + wg * 8, b + wg * nb, wp ^ tshift);
    __syncwarp();
  }
  Params P;
  {
    const float4 p0 = __ldcg(reinterpret_cast<const float4*>(&g_par));
    P.cS_t = p0.x; P.cS_s = p0.y; P.kt = p0.z; P.kappa = p0.w;
    P.sgmin = fmaxf(0.0045f, P.kappa * 0.011f);
  }
  const bool scaled = __any_sync(0xffffffffu, P.cS_s != 1.f);
  const bool direct = __all_sync(0xffffffffu, (P.cS_t == 1.f) & (P.kt <= 256.f) & (P.kappa <= 16.f));
  const int widx = __popc(((ROLE >> wg) & 1 ? ROLE : ~ROLE) & ((1 << wg) - 1));
  if ((ROLE >> wg) & 1) {
    loop_T(sb, nw, widx, wp, lane, P, direct TRPASS(g_trace + (b * 16 + wg * 4 + wp) * 1024));
  } else {
    loop_S(sb, nw, half, wlast, widx, tshift, wp, lane, P, scaled, &tm, out TRPASS(g_trace + (b * 16 + wg * 4 + wp) * 1024));
  }
}

__device__ __forceinline__ int ch_pos(int ch) { return 32 * (ch >> 5) + 4 * (ch & 4) + 8 * (ch & 1) + 2 * ((ch >> 3) & 3) + ((ch >> 1) & 1); }
__device__ __forceinline__ float pow2_ceil(float v) {
  return __uint_as_float((__float_as_uint(v) + 0x7fffffu) & 0x7f800000u);
}

constexpr int kPrepSplit = 12;
constexpr int kPrepThreads = 384;
__global__ void __launch_bounds__(kPrepThreads) swin_prep(const __nv_bfloat16* __restrict__ wqkv_t, const __nv_bfloat16* __restrict__ wo_t,
                                                          const __nv_bfloat16* __restrict__ wqkv_s, const __nv_bfloat16* __restrict__ wo_s) {
  asm volatile("griddepcontrol.launch_dependents;");
  __shared__ __align__(16) uint32_t raw[2][96][52];
  __shared__ __align__(16) uint32_t mu[3][52];
  __shared__ float nrm[12], nrm2[6], csum[6][9];
  const int mat = blockIdx.x / kPrepSplit, blk = blockIdx.x % kPrepSplit;
  const int tid = threadIdx.x, lane = tid & 31, warp = tid >> 5, g = lane >> 2, c = lane & 3;
  const __nv_bfloat16* wqkv = mat < 2 ? wqkv_t : wqkv_s;
  const __nv_bfloat16* wo = mat < 2 ? wo_t : wo_s;
  const bool isA = (mat & 1) == 0;
  {
    uint4 v[3], u[3];
#pragma unroll
    for (int q = 0; q < 3; q++) {
      const int e = tid + q * kPrepThreads, i = e / 12, c8 = (e % 12) * 8;
      v[q] = __ldg(reinterpret_cast<const uint4*>(wqkv + i * 288 + (isA ? 0 : 192) + c8));
      u[q] = __ldg(reinterpret_cast<const uint4*>(isA ? wqkv + i * 288 + 96 + c8 : wo + i * 96 + c8));
    }
#pragma unroll
    for (int q = 0; q < 3; q++) {
      const int e = tid + q * kPrepThreads, i = e / 12, c4 = (e % 12) * 4;
      *reinterpret_cast<uint4*>(&raw[0][i][c4]) = v[q];
      *reinterpret_cast<uint4*>(&raw[1][i][c4]) = u[q];
    }
  }
  __syncthreads();
  {
    const int m = warp / 6, cp = (warp % 6) * 8 + g;
    float s0 = 0.f, s1 = 0.f, q0 = 0.f, q1 = 0.f;
#pragma unroll
    for (int i = 0; i < 24; i++) {
      const uint32_t w = raw[m][4 * i + c][cp];
      const float lo = __uint_as_float(w << 16), hi = __uint_as_float(w & 0xffff0000u);
      s0 += lo; s1 += hi; q0 = fmaf(lo, lo, q0); q1 = fmaf(hi, hi, q1);
    }
    s0 = quad_sum(s0) * (1.f / 96.f); s1 = quad_sum(s1) * (1.f / 96.f); q0 = quad_sum(q0); q1 = quad_sum(q1);
    if (mat == 1 && m == 1) {
      float r0 = 0.f, r1 = 0.f;
#pragma unroll
      for (int i = 0; i < 12; i++) {
        const uint32_t w0 = raw[1][2 * cp][4 * i + c], w1 = raw[1][2 * cp + 1][4 * i + c];
        r0 += __uint_as_float(w0 << 16) + __uint_as_float(w0 & 0xffff0000u);
        r1 += __uint_as_float(w1 << 16) + __uint_as_float(w1 & 0xffff0000u);
      }
      r0 = quad_sum(r0) * (1.f / 96.f); r1 = quad_sum(r1) * (1.f / 96.f);
      s0 = r0; s1 = r1;
    }
    if (m == 1 && c == 0) {
      const uint32_t hi = mat == 3 ? 0u : pack_bf2(s0, s1);
      mu[0][cp] = hi;
      mu[1][cp] = mat == 3 ? 0u : pack_bf2(s0 - __uint_as_float(hi << 16), s1 - __uint_as_float(hi & 0xffff0000u));
      mu[2][cp] = 0u;
    }
    if (m == 0 || isA) {
      q0 = fmaxf(fmaf(-96.f * s0, s0, q0), 0.f) + q0 * 1e-6f;
      q1 = fmaxf(fmaf(-96.f * s1, s1, q1), 0.f) + q1 * 1e-6f;
    }
    const bool usemax = m == 1 && mat == 3;
    float t = usemax ? fmaxf(q0, q1) : q0 + q1;
#pragma unroll
    for (int o = 4; o < 32; o <<= 1) { const float z = __shfl_xor_sync(0xffffffffu, t, o); t = usemax ? fmaxf(t, z) : t + z; }
    if (lane == 0) nrm[warp] = t;
  }
  __syncthreads();
  if (warp >= 6) return;
  float d[4] = {0.f, 0.f, 0.f, 0.f}, e[4] = {0.f, 0.f, 0.f, 0.f}, v0, v1;
  {
    const uint32_t arow = smem_u32(&raw[0][16 * warp + (lane & 15)][(lane >> 4) * 4]);
    const uint32_t brow = isA ? smem_u32(&raw[1][blk * 8 + (lane & 7)][(lane >> 3) * 4]) : smem_u32(&raw[1][lane][blk * 4]);
    const uint32_t mrow = smem_u32(&mu[min(lane & 7, 2)][(lane >> 3) * 4]);
#pragma unroll
    for (int k2 = 0; k2 < 3; k2++) {
      uint32_t b[4], m[4];
      if (isA) ldsm4(b, brow + k2 * 64);
      else asm volatile("ldmatrix.sync.aligned.m8n8.x4.trans.shared.b16 {%0,%1,%2,%3}, [%4];"
                        : "=r"(b[0]), "=r"(b[1]), "=r"(b[2]), "=r"(b[3]) : "r"(brow + k2 * (32 * 208)) : "memory");
      ldsm4(m, mrow + k2 * 64);
#pragma unroll
      for (int hf = 0; hf < 2; hf++) {
        uint32_t a[4];
        ldsm4(a, arow + (2 * k2 + hf) * 32);
        asm volatile("mma.sync.aligned.m16n8k16.row.col.f32.bf16.bf16.f32 {%0,%1,%2,%3},{%4,%5,%6,%7},{%8,%9},{%0,%1,%2,%3};"
                     : "+f"(d[0]), "+f"(d[1]), "+f"(d[2]), "+f"(d[3])
                     : "r"(a[0]), "r"(a[1]), "r"(a[2]), "r"(a[3]), "r"(b[2 * hf]), "r"(b[2 * hf + 1]));
        asm volatile("mma.sync.aligned.m16n8k16.row.col.f32.bf16.bf16.f32 {%0,%1,%2,%3},{%4,%5,%6,%7},{%8,%9},{%0,%1,%2,%3};"
                     : "+f"(e[0]), "+f"(e[1]), "+f"(e[2]), "+f"(e[3])
                     : "r"(a[0]), "r"(a[1]), "r"(a[2]), "r"(a[3]), "r"(m[2 * hf]), "r"(m[2 * hf + 1]));
      }
    }
    v0 = __shfl_sync(0xffffffffu, e[0] + e[1], lane & ~3); v1 = __shfl_sync(0xffffffffu, e[2] + e[3], lane & ~3);
    d[0] -= v0; d[1] -= v0; d[2] -= v1; d[3] -= v1;
    float t0 = d[0] + d[2], t1 = d[1] + d[3], t2 = v0 + v1;
#pragma unroll
    for (int o = 4; o < 32; o <<= 1) {
      t0 += __shfl_xor_sync(0xffffffffu, t0, o); t1 += __shfl_xor_sync(0xffffffffu, t1, o); t2 += __shfl_xor_sync(0xffffffffu, t2, o);
    }
    if (g == 0) { csum[warp][2 * c] = t0; csum[warp][2 * c + 1] = t1; csum[warp][8] = t2; }
  }
  const float nl = nrm[0] + nrm[1] + nrm[2] + nrm[3] + nrm[4] + nrm[5];
  const float nr = mat == 3 ? fmaxf(fmaxf(fmaxf(nrm[6], nrm[7]), fmaxf(nrm[8], nrm[9])), fmaxf(nrm[10], nrm[11]))
                            : nrm[6] + nrm[7] + nrm[8] + nrm[9] + nrm[10] + nrm[11];
  const float bound = __fsqrt_rn(nl) * __fsqrt_rn(nr) * 1.01f;
  const float f = isA ? 0.14724448f : 1.f;
  float sc = pow2_ceil(fmaxf(bound * (isA ? 0.14724448f / 160.f : mat == 1 ? 1.f / 16.f : 1.f / 64.f), 1e-30f));
  if (isA) sc = fminf(fmaxf(sc, 1.f), 32768.f);
  const float mul = f * __uint_as_float(0x7f000000u - __float_as_uint(sc));
  if (blk == 0 && tid == 0) (mat == 0 ? g_par.cS_t : mat == 1 ? g_par.kt : mat == 2 ? g_par.cS_s : g_par.kappa) = sc;
  asm volatile("bar.sync 1, 192;" ::: "memory");
  float mean[2];
#pragma unroll
  for (int b = 0; b < 2; b++)
    mean[b] = (csum[0][2 * c + b] + csum[1][2 * c + b] + csum[2][2 * c + b] + csum[3][2 * c + b] + csum[4][2 * c + b] + csum[5][2 * c + b]) *
              (1.f / 96.f);
  uint8_t* img = reinterpret_cast<uint8_t*>(g_wimg) + (mat == 0 ? 0 : mat == 1 ? kOffWt : mat == 2 ? kOffAs : kOffWs);
  const float vmean = (csum[0][8] + csum[1][8] + csum[2][8] + csum[3][8] + csum[4][8] + csum[5][8]) * (1.f / 96.f);
  float off = 0.f;
  if (mat == 2) {
    float q2 = 0.f;
#pragma unroll
    for (int q = 0; q < 4; q++) q2 = fmaf(d[q] - mean[q & 1], d[q] - mean[q & 1], q2);
#pragma unroll
    for (int o = 16; o; o >>= 1) q2 += __shfl_xor_sync(0xffffffffu, q2, o);
    if (lane == 0) nrm2[warp] = q2;
    asm volatile("bar.sync 1, 192;" ::: "memory");
    q2 = nrm2[0] + nrm2[1] + nrm2[2] + nrm2[3] + nrm2[4] + nrm2[5];
    off = 1.5f * pow2_ceil(fmaxf(__fsqrt_rn(q2 * (1.f / 768.f)) * mul * 3.f, 1e-4f));
  }
#pragma unroll
  for (int q = 0; q < 4; q++) {
    const int kp = ch_pos(16 * warp + g + 8 * (q >> 1)), np = ch_pos(blk * 8 + 2 * c + (q & 1));
    const uint32_t ko = (kp >> 5) * (mat == 0 ? kAtChunk : 6144) + (kp & 31) * 2;
    uint32_t a = ko + np * 64;
    a ^= ((a >> 7) & 3) << 4;
    float o = (d[q] - mean[q & 1]) * mul;
    o = mat == 2 ? o + off : __uint_as_float((__float_as_uint(o) + 0x8000u) & 0xffff0000u);
    *reinterpret_cast<__half*>(img + a) = __float2half_rn(o);
    if (mat == 1 && blk == 0) {
      a = (kp >> 5) * kAtChunk + (kp & 31) * 2 + (96 + 2 * c + (q & 1)) * 64;
      a ^= ((a >> 7) & 3) << 4;
      *reinterpret_cast<__half*>(reinterpret_cast<uint8_t*>(g_wimg) + a) = __float2half_rn((q & 1) ? ((q >> 1 ? v1 : v0) - vmean) * mul : 1.f / 96.f);
    }
  }
}

typedef CUresult (*EncodeFn)(CUtensorMap*, CUtensorMapDataType, cuuint32_t, void*, const cuuint64_t*, const cuuint64_t*,
                             const cuuint32_t*, const cuuint32_t*, CUtensorMapInterleave, CUtensorMapSwizzle,
                             CUtensorMapL2promotion, CUtensorMapFloatOOBfill);

}

extern "C" void kernel_launch(void* const* d_in, const int* in_sizes, int n_in, void* d_out, int out_size) {
  (void)in_sizes; (void)n_in; (void)out_size;
  static EncodeFn enc = nullptr;
  static int nsm = 0;
  if (!enc) {
    void* fn = nullptr;
    cudaDriverEntryPointQueryResult qr;
    cudaGetDriverEntryPoint("cuTensorMapEncodeTiled", &fn, cudaEnableDefault, &qr);
    enc = reinterpret_cast<EncodeFn>(fn);
    int dev = 0;
    cudaGetDevice(&dev);
    cudaDeviceGetAttribute(&nsm, cudaDevAttrMultiProcessorCount, dev);
    cudaFuncSetAttribute(swin_main, cudaFuncAttributeMaxDynamicSharedMemorySize, kSmemBytes);
  }
  Maps maps;
  CUtensorMap& tm = maps.tm;
  const cuuint64_t dims[5] = {32, kW, kH, kT, 3};
  const cuuint64_t strides[4] = {192, 192ull * kW, 192ull * kW * kH, 64};
  const cuuint32_t box[5] = {32, 7, 7, 1, 3};
  const cuuint32_t es[5] = {1, 1, 1, 1, 1};
  enc(&tm, CU_TENSOR_MAP_DATA_TYPE_BFLOAT16, 5, d_in[0], dims, strides, box, es, CU_TENSOR_MAP_INTERLEAVE_NONE,
      CU_TENSOR_MAP_SWIZZLE_64B, CU_TENSOR_MAP_L2_PROMOTION_L2_128B, CU_TENSOR_MAP_FLOAT_OOB_FILL_NONE);
  {
    const cuuint64_t d3[3] = {24 * kW, kH, kT};
    const cuuint64_t s3[2] = {192ull * kW, 192ull * kW * kH};
    const cuuint32_t b3[3] = {168, 7, 1};
    enc(&maps.pf, CU_TENSOR_MAP_DATA_TYPE_INT64, 3, d_in[0], d3, s3, b3, es, CU_TENSOR_MAP_INTERLEAVE_NONE,
        CU_TENSOR_MAP_SWIZZLE_NONE, (CUtensorMapL2promotion)PRM, CU_TENSOR_MAP_FLOAT_OOB_FILL_NONE);
  }

  cudaStream_t st = cudaStreamPerThread;
  swin_prep<<<4 * kPrepSplit, kPrepThreads, 0, st>>>(
      static_cast<const __nv_bfloat16*>(d_in[1]), static_cast<const __nv_bfloat16*>(d_in[2]),
      static_cast<const __nv_bfloat16*>(d_in[3]), static_cast<const __nv_bfloat16*>(d_in[4]));

  cudaLaunchConfig_t cfg = {};
  cfg.gridDim = dim3(nsm);
  cfg.blockDim = dim3(kNWG * 128);
  cfg.dynamicSmemBytes = kSmemBytes;
  cfg.stream = st;
  cudaLaunchAttribute at[1];
  at[0].id = cudaLaunchAttributeProgrammaticStreamSerialization;
  at[0].val.programmaticStreamSerializationAllowed = 1;
  cfg.attrs = at;
  cfg.numAttrs = 1;
  cudaLaunchKernelEx(&cfg, swin_main, maps, static_cast<uint8_t*>(d_out));
}
```

```cpp
#include <cuda_runtime.h>
#include <cuda.h>
#include <cuda_bf16.h>
#include <cuda_fp16.h>
#include <stdint.h>

#define LB 512
#define SF 17
#define TIE 0
#define SG 1
#define IL 1
#define FP 2
#define ROLE 3
#define RF 2
#define CK0 0
#define LIKELY(x) __builtin_expect(!!(x), 1)
#define UNLIKELY(x) __builtin_expect(!!(x), 0)
#define CV 1
#define C1 2
#define C2 2
#define WS 1
#define TL 1
#define PAD 0
#define SPL 1
#define SPN 64
#define SPO 1
#define LD 1
#define DA 1
#define E1 0
#define E2 0
#define E3 0
#define E4 0
#define G4 0
#define BE 0
#define CS 0
#define QP 3
#define PG 3
#define PR 4
#define PF0 1
#define EARLY 0
#define PF 2
#define HQ 0
#define PRM 2
#define CM 0
#define AB 0
#define ST 0
#define WF 0
#define NWH 25
#define DYN 1
#define EL 0
#define HD 0
#define OA 3
#define OB 1
#define OC 1
#define OH 1
#define XE 0
namespace {

constexpr int kH = 511, kW = 511, kT = 4;
constexpr int kNWX = 73, kNWIN = 73 * 73;
constexpr int kChunk = 3136;
constexpr int kXBytes = 3 * kChunk;
constexpr int kFrame = 9728;
constexpr int kBufStride = 4 * kFrame;
constexpr uint32_t kPadStat = 0x7bff;
constexpr int kWMat = 18432;
constexpr int kAtChunk = 104 * 64;
constexpr int kOffWt = 3 * kAtChunk;
constexpr int kOffAs = kOffWt + kWMat, kOffWs = kOffAs + kWMat;
constexpr int kWBytes = kOffWs + kWMat;
constexpr int kOffBuf = kWBytes;
constexpr int kOffBar = kOffBuf + 4 * kBufStride + 640;
constexpr int kOffFlag = kOffBar + 64;
constexpr int kOffBarW = kOffBar + 80;
constexpr int kOffBarB = kOffBar + 96;
constexpr int kOffCs = kOffBar + 128;
constexpr int kOffClaim = kOffBar + 132;
constexpr int kSmemBytes = kOffBar + 144;
constexpr int kNWG = 4;

struct Maps { CUtensorMap tm, pf; };
struct Params {
  float cS_t, cS_s;
  float kt;
  float kappa;
  float sgmin;
};

__device__ uint4 g_wimg[kWBytes / 16];
__device__ __align__(16) Params g_par;
__device__ uint32_t g_ctr;

#define TR(idx)
#define TRARG
#define TRPASS(x)
__device__ __forceinline__ uint32_t smem_u32(const void* p) { return (uint32_t)__cvta_generic_to_shared(p); }
__device__ __forceinline__ void mbar_init(uint32_t a, int c) { asm volatile("mbarrier.init.shared::cta.b64 [%0], %1;" ::"r"(a), "r"(c)); }
__device__ __forceinline__ void mbar_expect(uint32_t a, int bytes) {
  asm volatile("mbarrier.arrive.expect_tx.shared::cta.b64 _, [%0], %1;" ::"r"(a), "r"(bytes) : "memory");
}
__device__ __forceinline__ void mbar_arrive(uint32_t a) {
  asm volatile("mbarrier.arrive.shared::cta.b64 _, [%0];" ::"r"(a) : "memory");
}
__device__ __forceinline__ void mbar_wait(uint32_t a, uint32_t par) {
  asm volatile(
      "{\n.reg .pred p;\n.reg .u32 n;\n"
      "mbarrier.try_wait.parity.shared::cta.b64 p, [%0], %1;\n"
      "@p bra.uni WDONE;\n"
      "mov.u32 n, 0;\n"
      "WLOOP:\n"
      "mbarrier.try_wait.parity.shared::cta.b64 p, [%0], %1;\n"
      "@p bra.uni WDONE;\n"
      "add.u32 n, n, 1;\n"
      "setp.lt.u32 p, n, 0x1000000;\n"
      "@p bra.uni WLOOP;\n"
      "trap;\n"
      "WDONE:\n}" ::"r"(a), "r"(par) : "memory");
}
__device__ __forceinline__ void tma_load(uint32_t dst, const CUtensorMap* m, uint32_t bar, uint32_t w, uint32_t t) {
  const uint32_t wy = (w * 57457u) >> 22, wx = w - wy * kNWX;
  mbar_expect(bar, kXBytes);
  asm volatile(
      "cp.async.bulk.tensor.5d.shared::cluster.global.mbarrier::complete_tx::bytes [%0], [%1, {%3,%4,%5,%6,%3}], [%2];" ::"r"(dst),
      "l"(m), "r"(bar), "r"(0), "r"(wx * 7), "r"(wy * 7), "r"(t)
      : "memory");
}
__device__ __forceinline__ void tma_prefetch(const CUtensorMap* m, uint32_t w, uint32_t t) {
  const uint32_t wy = (w * 57457u) >> 22, wx = w - wy * kNWX;
  asm volatile("cp.async.bulk.prefetch.tensor.3d.L2.global [%0, {%1,%2,%3}];" ::"l"(m + 1), "r"(wx * 168), "r"(wy * 7), "r"(t) : "memory");
}
template <bool kPrefetch>
__device__ __forceinline__ void tma_load_elect(uint32_t dst, const CUtensorMap* m, uint32_t bar, uint32_t w, uint32_t t, uint32_t tp) {
  const uint32_t wy = (w * 57457u) >> 22, wx = w - wy * kNWX;
  asm volatile("{\n.reg .pred p;\nelect.sync _|p, 0xffffffff;\n"
               "@p mbarrier.arrive.expect_tx.shared::cta.b64 _, [%2], %7;\n"
               "@p cp.async.bulk.tensor.5d.shared::cluster.global.mbarrier::complete_tx::bytes [%0], [%1, {%3,%4,%5,%6,%3}], [%2];\n}"
               ::"r"(dst), "l"(m), "r"(bar), "r"(0), "r"(wx * 7), "r"(wy * 7), "r"(t), "n"(kXBytes) : "memory");
  if (kPrefetch)
    asm volatile("{\n.reg .pred p;\nelect.sync _|p, 0xffffffff;\n@p cp.async.bulk.prefetch.tensor.3d.L2.global [%0, {%1,%2,%3}];\n}"
                 ::"l"(m + 1), "r"(wx * 168), "r"(wy * 7), "r"(tp) : "memory");
}
__device__ __forceinline__ void wg_fence() { asm volatile("wgmma.fence.sync.aligned;" ::: "memory"); }
__device__ __forceinline__ void wg_commit() { asm volatile("wgmma.commit_group.sync.aligned;" ::: "memory"); }
template <int N>
__device__ __forceinline__ void wg_wait() { asm volatile("wgmma.wait_group.sync.aligned %0;" ::"n"(N) : "memory"); }
template <int N>
__device__ __forceinline__ void pin(uint32_t* d) {
#pragma unroll
  for (int i = 0; i < N; i++) asm volatile("" : "+r"(d[i])::"memory");
}
__device__ __forceinline__ void sched_fence(uint32_t a, uint32_t b, uint32_t c) {
  asm volatile("{\n.reg .pred p;\n.reg .b32 t;\nsetp.ne.u32 p, %0, 0x7fffffff;\n@p bra.uni SFD;\n"
               "add.u32 t, %1, %2;\nadd.u32 t, t, %3;\nnanosleep.u32 t;\nSFD:\n}" ::"r"(gridDim.x), "r"(a), "r"(b), "r"(c) : "memory");
}
__device__ __forceinline__ void hold(uint32_t sb, uint32_t v) {
  asm volatile("{\n.reg .pred p;\nsetp.eq.u32 p, %0, 0x7fffffff;\n@p st.volatile.shared.b32 [%1], %2;\n}" ::"r"(gridDim.x), "r"(sb), "r"(v) : "memory");
}
__device__ __forceinline__ uint64_t mk_desc(uint32_t addr, uint32_t lbo16) {
  return ((uint64_t)0x80000020u << 32) | ((addr >> 4) & 0x3fff) | (lbo16 << 16);
}

__device__ __forceinline__ uint64_t desc_at(uint32_t lo) { return ((uint64_t)0x80000020u << 32) | lo; }

#define R4(d, i) "+r"(d[i]), "+r"(d[i + 1]), "+r"(d[i + 2]), "+r"(d[i + 3])
#define O4(d, i) "=r"(d[i]), "=r"(d[i + 1]), "=r"(d[i + 2]), "=r"(d[i + 3])
#define D24 "{%0,%1,%2,%3,%4,%5,%6,%7,%8,%9,%10,%11,%12,%13,%14,%15,%16,%17,%18,%19,%20,%21,%22,%23},"
#define D14 "{%0,%1,%2,%3,%4,%5,%6,%7,%8,%9,%10,%11,%12,%13},"

template <int SC, int TB>
__device__ __forceinline__ void wg96h(uint32_t (&d)[24], const uint32_t* a, uint64_t db, uint32_t acc = 0) {
  if (SC == 2)
    asm volatile("{\n.reg .pred p;\nsetp.ne.u32 p, %30, 0;\n"
                 "wgmma.mma_async.sync.aligned.m64n96k16.f16.f16.f16 " D24 "{%24,%25,%26,%27}, %28, p, 1, 1, %29;\n}"
                 : R4(d, 0), R4(d, 4), R4(d, 8), R4(d, 12), R4(d, 16), R4(d, 20)
                 : "r"(a[0]), "r"(a[1]), "r"(a[2]), "r"(a[3]), "l"(db), "n"(TB), "r"(acc));
  else if (SC)
    asm volatile("wgmma.mma_async.sync.aligned.m64n96k16.f16.f16.f16 " D24 "{%24,%25,%26,%27}, %28, 1, 1, 1, %29;"
                 : R4(d, 0), R4(d, 4), R4(d, 8), R4(d, 12), R4(d, 16), R4(d, 20)
                 : "r"(a[0]), "r"(a[1]), "r"(a[2]), "r"(a[3]), "l"(db), "n"(TB));
  else
    asm volatile("wgmma.mma_async.sync.aligned.m64n96k16.f16.f16.f16 " D24 "{%24,%25,%26,%27}, %28, 0, 1, 1, %29;"
                 : O4(d, 0), O4(d, 4), O4(d, 8), O4(d, 12), O4(d, 16), O4(d, 20)
                 : "r"(a[0]), "r"(a[1]), "r"(a[2]), "r"(a[3]), "l"(db), "n"(TB));
}
template <int SC>
__device__ __forceinline__ void wg104h(uint32_t (&d)[26], const uint32_t* a, uint64_t db) {
  if (SC)
    asm volatile("wgmma.mma_async.sync.aligned.m64n104k16.f16.f16.f16 "
                 "{%0,%1,%2,%3,%4,%5,%6,%7,%8,%9,%10,%11,%12,%13,%14,%15,%16,%17,%18,%19,%20,%21,%22,%23,%24,%25},"
                 "{%26,%27,%28,%29}, %30, 1, 1, 1, 0;"
                 : R4(d, 0), R4(d, 4), R4(d, 8), R4(d, 12), R4(d, 16), R4(d, 20), "+r"(d[24]), "+r"(d[25])
                 : "r"(a[0]), "r"(a[1]), "r"(a[2]), "r"(a[3]), "l"(db));
  else
    asm volatile("wgmma.mma_async.sync.aligned.m64n104k16.f16.f16.f16 "
                 "{%0,%1,%2,%3,%4,%5,%6,%7,%8,%9,%10,%11,%12,%13,%14,%15,%16,%17,%18,%19,%20,%21,%22,%23,%24,%25},"
                 "{%26,%27,%28,%29}, %30, 0, 1, 1, 0;"
                 : O4(d, 0), O4(d, 4), O4(d, 8), O4(d, 12), O4(d, 16), O4(d, 20), "=r"(d[24]), "=r"(d[25])
                 : "r"(a[0]), "r"(a[1]), "r"(a[2]), "r"(a[3]), "l"(db));
}
template <int SC>
__device__ __forceinline__ void wg56h(uint32_t* d, const uint32_t* a, uint64_t db) {
  if (SC)
    asm volatile("wgmma.mma_async.sync.aligned.m64n56k16.f16.f16.f16 " D14 "{%14,%15,%16,%17}, %18, 1, 1, 1, 0;"
                 : R4(d, 0), R4(d, 4), R4(d, 8), "+r"(d[12]), "+r"(d[13])
                 : "r"(a[0]), "r"(a[1]), "r"(a[2]), "r"(a[3]), "l"(db));
  else
    asm volatile("wgmma.mma_async.sync.aligned.m64n56k16.f16.f16.f16 " D14 "{%14,%15,%16,%17}, %18, 0, 1, 1, 0;"
                 : O4(d, 0), O4(d, 4), O4(d, 8), "=r"(d[12]), "=r"(d[13])
                 : "r"(a[0]), "r"(a[1]), "r"(a[2]), "r"(a[3]), "l"(db));
}
template <int SC>
__device__ __forceinline__ void gemm_w(uint32_t (&d)[24], const uint32_t* a, uint64_t dw, uint32_t acc = 0) {
  wg_fence();
  wg96h<SC, 0>(d, a, dw, acc); wg96h<1, 0>(d, a + 4, dw + 2);
  wg96h<1, 0>(d, a + 8, dw + 384); wg96h<1, 0>(d, a + 12, dw + 386);
  wg96h<1, 0>(d, a + 16, dw + 768); wg96h<1, 0>(d, a + 20, dw + 770);
  wg_commit();
}
__device__ __forceinline__ void lds128(uint32_t* r, uint32_t a) {
  asm volatile("ld.shared.v4.b32 {%0,%1,%2,%3}, [%4];" : "=r"(r[0]), "=r"(r[1]), "=r"(r[2]), "=r"(r[3]) : "r"(a) : "memory");
}
__device__ __forceinline__ uint32_t lds32(uint32_t a) {
  uint32_t r; asm volatile("ld.volatile.shared.b32 %0, [%1];" : "=r"(r) : "r"(a) : "memory"); return r;
}
__device__ __forceinline__ void sts32(uint32_t a, uint32_t v) { asm volatile("st.volatile.shared.b32 [%0], %1;" ::"r"(a), "r"(v) : "memory"); }
__device__ __forceinline__ void ldsm4(uint32_t* r, uint32_t a) {
  asm volatile("ldmatrix.sync.aligned.m8n8.x4.shared.b16 {%0,%1,%2,%3}, [%4];"
               : "=r"(r[0]), "=r"(r[1]), "=r"(r[2]), "=r"(r[3]) : "r"(a) : "memory");
}
__device__ __forceinline__ void stsm4(uint32_t a, const uint32_t* r) {
  asm volatile("stmatrix.sync.aligned.m8n8.x4.shared.b16 [%0], {%1,%2,%3,%4};" ::"r"(a), "r"(r[0]), "r"(r[1]), "r"(r[2]), "r"(r[3])
               : "memory");
}
__device__ __forceinline__ uint32_t pack_h2(float lo, float hi) {
  uint32_t r; asm("cvt.rn.f16x2.f32 %0, %1, %2;" : "=r"(r) : "f"(hi), "f"(lo)); return r;
}
__device__ __forceinline__ uint32_t pack_h2_rz(float lo, float hi) {
  uint32_t r; asm("cvt.rz.f16x2.f32 %0, %1, %2;" : "=r"(r) : "f"(hi), "f"(lo)); return r;
}
__device__ __forceinline__ uint32_t pack_h2_sat(float lo, float hi) {
  uint32_t r; asm("cvt.rn.satfinite.f16x2.f32 %0, %1, %2;" : "=r"(r) : "f"(hi), "f"(lo)); return r;
}
__device__ __forceinline__ uint32_t pack_bf2(float lo, float hi) {
  uint32_t r; asm("cvt.rn.bf16x2.f32 %0, %1, %2;" : "=r"(r) : "f"(hi), "f"(lo)); return r;
}
__device__ __forceinline__ __half2 as_h2(uint32_t v) { return *reinterpret_cast<__half2*>(&v); }
__device__ __forceinline__ uint32_t as_u(__half2 v) { return *reinterpret_cast<uint32_t*>(&v); }
__device__ __forceinline__ float2 unpack_h2(uint32_t v) { return __half22float2(as_h2(v)); }
__device__ __forceinline__ uint32_t h2ex2(uint32_t v) { uint32_t r; asm("ex2.approx.f16x2 %0, %1;" : "=r"(r) : "r"(v)); return r; }
__device__ __forceinline__ uint32_t h2max(uint32_t a, uint32_t b) { return as_u(__hmax2(as_h2(a), as_h2(b))); }
__device__ __forceinline__ uint32_t h2add(uint32_t a, uint32_t b) { return as_u(__hadd2(as_h2(a), as_h2(b))); }
__device__ __forceinline__ uint32_t h2sub(uint32_t a, uint32_t b) { return as_u(__hsub2(as_h2(a), as_h2(b))); }
__device__ __forceinline__ uint32_t h2mul(uint32_t a, uint32_t b) { return as_u(__hmul2(as_h2(a), as_h2(b))); }
__device__ __forceinline__ uint32_t h2fma(uint32_t a, uint32_t b, uint32_t c) { return as_u(__hfma2(as_h2(a), as_h2(b), as_h2(c))); }
__device__ __forceinline__ uint32_t lo2(uint32_t v) { return as_u(__low2half2(as_h2(v))); }
__device__ __forceinline__ uint32_t hi2(uint32_t v) { return as_u(__high2half2(as_h2(v))); }
__device__ __forceinline__ uint32_t fold_add(uint32_t a, uint32_t b) { return h2add(__byte_perm(a, b, 0x5410), __byte_perm(a, b, 0x7632)); }
__device__ __forceinline__ uint32_t bitsel(uint32_t a, uint32_t m, uint32_t c) {
  uint32_t r; asm("lop3.b32 %0, %1, %2, %3, 0xe2;" : "=r"(r) : "r"(a), "r"(m), "r"(c)); return r;
}
__device__ __forceinline__ float rcp_fast(float v) { float r; asm("rcp.approx.ftz.f32 %0, %1;" : "=f"(r) : "f"(v)); return r; }
__device__ __forceinline__ float rsq_fast(float v) { float r; asm("rsqrt.approx.ftz.f32 %0, %1;" : "=f"(r) : "f"(v)); return r; }
__device__ __forceinline__ float quad_sum(float v) {
  v += __shfl_xor_sync(0xffffffffu, v, 1);
  return v + __shfl_xor_sync(0xffffffffu, v, 2);
}
__device__ __forceinline__ uint32_t quad_h2add(uint32_t v) {
  v = h2add(v, __shfl_xor_sync(0xffffffffu, v, 1));
  return h2add(v, __shfl_xor_sync(0xffffffffu, v, 2));
}
__device__ __forceinline__ uint32_t score_scale(const float* p) { const float v = __ldcg(p); return pack_h2(v, v); }

constexpr float kEps96 = 1e-5f * 96.f * 96.f;
__device__ __forceinline__ float2 stat_f32(uint32_t e) {
  const float2 h = unpack_h2(e);
  return make_float2((e & 0x8000u) ? __uint_as_float((e << 16) & 0x7fff0000u) : h.x, (e & 0x8000u) ? __uint_as_float(e & 0xffff0000u) : h.y);
}

__device__ __forceinline__ uint32_t swz(uint32_t a) { return a ^ ((a >> 3) & 0x30); }
__device__ __forceinline__ uint32_t prmt(uint32_t a, uint32_t b, uint32_t s) {
  uint32_t r; asm("prmt.b32 %0, %1, %2, %3;" : "=r"(r) : "r"(a), "r"(b), "r"(s)); return r;
}
__device__ __forceinline__ void tie48(uint32_t* a, uint32_t* b, uint64_t d, uint32_t u = 0, uint32_t v = 0) {
  asm volatile("{\n.reg .pred p;\n.reg .b32 t;\nsetp.ne.u32 p, %48, 0x7fffffff;\n@p bra.uni TIED;\n"
               "wgmma.fence.sync.aligned;\n"
               "wgmma.mma_async.sync.aligned.m64n192k16.f16.f16.f16 {%0,%1,%2,%3,%4,%5,%6,%7,%8,%9,%10,%11,%12,%13,%14,%15,%16,%17,%18,%19,%20,%21,%22,%23,%24,%25,%26,%27,%28,%29,%30,%31,%32,%33,%34,%35,%36,%37,%38,%39,%40,%41,%42,%43,%44,%45,%46,%47}, %49, %49, 1, 1, 1, 0, 0;\n"
               "wgmma.commit_group.sync.aligned;\nwgmma.wait_group.sync.aligned 0;\nTIED:\n}"
               : R4(a, 0), R4(a, 4), R4(a, 8), R4(a, 12), R4(a, 16), R4(a, 20), R4(b, 0), R4(b, 4), R4(b, 8), R4(b, 12), R4(b, 16), R4(b, 20)
               : "r"(gridDim.x), "l"(d), "r"(u), "r"(v) : "memory");
}
template <int N>
__device__ __forceinline__ void x_delay(uint32_t v) {
  if (N == 0) return;
  asm volatile("{\n.reg .pred p;\nsetp.eq.u32 p, %0, 0x7fffffff;\n"
#define XL1 "vote.sync.any.pred p, p, 0xffffffff;\n"
               XL1 XL1 XL1 XL1 XL1 XL1 XL1 XL1
               "@!p bra.uni XD;\nnanosleep.u32 %0;\nXD:\n}" ::"r"(v) : "memory");
}
template <int N>
__device__ __forceinline__ void x_work(uint32_t v) {
  if (N == 0) return;
  uint32_t a = v, b = v + 1, c = v + 2, d = v + 3;
#pragma unroll
  for (int i = 0; i < N / 4; i++)
    asm volatile("fma.rn.f16x2 %0, %0, %4, %4;\nfma.rn.f16x2 %1, %1, %4, %4;\nfma.rn.f16x2 %2, %2, %4, %4;\nfma.rn.f16x2 %3, %3, %4, %4;" : "+r"(a), "+r"(b), "+r"(c), "+r"(d) : "r"(v));
  sched_fence(a ^ b, c, d);
}
struct A3 { uint32_t a[3]; };
__device__ __forceinline__ A3 swz3(uint32_t a) { return A3{{swz(a), swz(a + kChunk), swz(a + 2 * kChunk)}}; }
__device__ __forceinline__ void load_row(uint32_t* x, const A3& a, int t) {
  lds128(x, a.a[0] + t * kFrame); lds128(x + 4, a.a[1] + t * kFrame); lds128(x + 8, a.a[2] + t * kFrame);
}
__device__ __forceinline__ void row_to_h2(uint32_t* y, const uint32_t* x) {
#pragma unroll
  for (int j = 0; j < 12; j += 2) {
    y[2 * j] = pack_h2(__uint_as_float(x[j] << 16), __uint_as_float(x[j + 1] << 16));
    uint32_t r;
    asm("cvt.rz.f16x2.f32 %0, %1, %2;" : "=r"(r) : "f"(__uint_as_float(x[j + 1])), "f"(__uint_as_float(x[j])));
    y[2 * j + 2] = r & 0xfff8fff8u;
  }
}
__device__ __forceinline__ void gemm_at(uint32_t (&q)[26], const uint32_t* z, uint64_t da) {
  wg_fence();
  wg104h<0>(q, z, da); wg104h<1>(q, z + 4, da + 2);
  wg104h<1>(q, z + 8, da + 416); wg104h<1>(q, z + 12, da + 418);
  wg104h<1>(q, z + 16, da + 832); wg104h<1>(q, z + 20, da + 834);
  wg_commit();
}
template <int SC>
__device__ __forceinline__ void wg64h(uint32_t* d, const uint32_t* a, uint64_t db) {
  if (SC)
    asm volatile("wgmma.mma_async.sync.aligned.m64n64k16.f16.f16.f16 {%0,%1,%2,%3,%4,%5,%6,%7,%8,%9,%10,%11,%12,%13,%14,%15}, {%16,%17,%18,%19}, %20, 1, 1, 1, 0;"
                 : "+r"(d[0]), "+r"(d[1]), "+r"(d[2]), "+r"(d[3]), "+r"(d[4]), "+r"(d[5]), "+r"(d[6]), "+r"(d[7]), "+r"(d[8]), "+r"(d[9]), "+r"(d[10]), "+r"(d[11]), "+r"(d[12]), "+r"(d[13]), "+r"(d[14]), "+r"(d[15])
                 : "r"(a[0]), "r"(a[1]), "r"(a[2]), "r"(a[3]), "l"(db));
  else
    asm volatile("wgmma.mma_async.sync.aligned.m64n64k16.f16.f16.f16 {%0,%1,%2,%3,%4,%5,%6,%7,%8,%9,%10,%11,%12,%13,%14,%15}, {%16,%17,%18,%19}, %20, 0, 1, 1, 0;"
                 : "=r"(d[0]), "=r"(d[1]), "=r"(d[2]), "=r"(d[3]), "=r"(d[4]), "=r"(d[5]), "=r"(d[6]), "=r"(d[7]), "=r"(d[8]), "=r"(d[9]), "=r"(d[10]), "=r"(d[11]), "=r"(d[12]), "=r"(d[13]), "=r"(d[14]), "=r"(d[15])
                 : "r"(a[0]), "r"(a[1]), "r"(a[2]), "r"(a[3]), "l"(db));
}
template <int SC>
__device__ __forceinline__ void wg40h(uint32_t* d, const uint32_t* a, uint64_t db) {
  if (SC)
    asm volatile("wgmma.mma_async.sync.aligned.m64n40k16.f16.f16.f16 {%0,%1,%2,%3,%4,%5,%6,%7,%8,%9}, {%10,%11,%12,%13}, %14, 1, 1, 1, 0;"
                 : "+r"(d[0]), "+r"(d[1]), "+r"(d[2]), "+r"(d[3]), "+r"(d[4]), "+r"(d[5]), "+r"(d[6]), "+r"(d[7]), "+r"(d[8]), "+r"(d[9])
                 : "r"(a[0]), "r"(a[1]), "r"(a[2]), "r"(a[3]), "l"(db));
  else
    asm volatile("wgmma.mma_async.sync.aligned.m64n40k16.f16.f16.f16 {%0,%1,%2,%3,%4,%5,%6,%7,%8,%9}, {%10,%11,%12,%13}, %14, 0, 1, 1, 0;"
                 : "=r"(d[0]), "=r"(d[1]), "=r"(d[2]), "=r"(d[3]), "=r"(d[4]), "=r"(d[5]), "=r"(d[6]), "=r"(d[7]), "=r"(d[8]), "=r"(d[9])
                 : "r"(a[0]), "r"(a[1]), "r"(a[2]), "r"(a[3]), "l"(db));
}
template <int SC>
__device__ __forceinline__ void wg80h(uint32_t* d, const uint32_t* a, uint64_t db) {
  if (SC)
    asm volatile("wgmma.mma_async.sync.aligned.m64n80k16.f16.f16.f16 {%0,%1,%2,%3,%4,%5,%6,%7,%8,%9,%10,%11,%12,%13,%14,%15,%16,%17,%18,%19}, {%20,%21,%22,%23}, %24, 1, 1, 1, 0;"
                 : "+r"(d[0]), "+r"(d[1]), "+r"(d[2]), "+r"(d[3]), "+r"(d[4]), "+r"(d[5]), "+r"(d[6]), "+r"(d[7]), "+r"(d[8]), "+r"(d[9]), "+r"(d[10]), "+r"(d[11]), "+r"(d[12]), "+r"(d[13]), "+r"(d[14]), "+r"(d[15]), "+r"(d[16]), "+r"(d[17]), "+r"(d[18]), "+r"(d[19])
                 : "r"(a[0]), "r"(a[1]), "r"(a[2]), "r"(a[3]), "l"(db));
  else
    asm volatile("wgmma.mma_async.sync.aligned.m64n80k16.f16.f16.f16 {%0,%1,%2,%3,%4,%5,%6,%7,%8,%9,%10,%11,%12,%13,%14,%15,%16,%17,%18,%19}, {%20,%21,%22,%23}, %24, 0, 1, 1, 0;"
                 : "=r"(d[0]), "=r"(d[1]), "=r"(d[2]), "=r"(d[3]), "=r"(d[4]), "=r"(d[5]), "=r"(d[6]), "=r"(d[7]), "=r"(d[8]), "=r"(d[9]), "=r"(d[10]), "=r"(d[11]), "=r"(d[12]), "=r"(d[13]), "=r"(d[14]), "=r"(d[15]), "=r"(d[16]), "=r"(d[17]), "=r"(d[18]), "=r"(d[19])
                 : "r"(a[0]), "r"(a[1]), "r"(a[2]), "r"(a[3]), "l"(db));
}
template <int SC>
__device__ __forceinline__ void wg24h(uint32_t* d, const uint32_t* a, uint64_t db) {
  if (SC)
    asm volatile("wgmma.mma_async.sync.aligned.m64n24k16.f16.f16.f16 {%0,%1,%2,%3,%4,%5}, {%6,%7,%8,%9}, %10, 1, 1, 1, 0;"
                 : "+r"(d[0]), "+r"(d[1]), "+r"(d[2]), "+r"(d[3]), "+r"(d[4]), "+r"(d[5])
                 : "r"(a[0]), "r"(a[1]), "r"(a[2]), "r"(a[3]), "l"(db));
  else
    asm volatile("wgmma.mma_async.sync.aligned.m64n24k16.f16.f16.f16 {%0,%1,%2,%3,%4,%5}, {%6,%7,%8,%9}, %10, 0, 1, 1, 0;"
                 : "=r"(d[0]), "=r"(d[1]), "=r"(d[2]), "=r"(d[3]), "=r"(d[4]), "=r"(d[5])
                 : "r"(a[0]), "r"(a[1]), "r"(a[2]), "r"(a[3]), "l"(db));
}
__device__ __forceinline__ void gemm_at2(uint32_t (&q)[26], const uint32_t* z, uint64_t da) {
  wg_fence();
#define WA wg64h
#define WB wg40h
  constexpr int o = SPN / 4, e = SPN * 4;
  WA<0>(q, z, da); WB<0>(q + o, z, da + e); WA<1>(q, z + 4, da + 2); WB<1>(q + o, z + 4, da + e + 2);
  WA<1>(q, z + 8, da + 416); WB<1>(q + o, z + 8, da + e + 416); WA<1>(q, z + 12, da + 418); WB<1>(q + o, z + 12, da + e + 418);
  WA<1>(q, z + 16, da + 832); WB<1>(q + o, z + 16, da + e + 832); WA<1>(q, z + 20, da + 834); WB<1>(q + o, z + 20, da + e + 834);
  wg_commit();
}
__device__ __forceinline__ void wg48h(uint32_t* d, const uint32_t* a, uint64_t db) {
  asm volatile("wgmma.mma_async.sync.aligned.m64n48k16.f16.f16.f16 {%0,%1,%2,%3,%4,%5,%6,%7,%8,%9,%10,%11}, {%12,%13,%14,%15}, %16, 1, 1, 1, 0;"
               : "+r"(d[0]), "+r"(d[1]), "+r"(d[2]), "+r"(d[3]), "+r"(d[4]), "+r"(d[5]), "+r"(d[6]), "+r"(d[7]), "+r"(d[8]), "+r"(d[9]), "+r"(d[10]), "+r"(d[11])
               : "r"(a[0]), "r"(a[1]), "r"(a[2]), "r"(a[3]), "l"(db));
}
__device__ __forceinline__ void gemm_w2(uint32_t* d, const uint32_t* a, uint64_t dw) {
  wg_fence();
#pragma unroll
  for (int k = 0; k < 6; k++) {
    wg48h(d, a + 4 * k, dw + (k >> 1) * 384 + (k & 1) * 2); wg48h(d + 12, a + 4 * k, dw + (k >> 1) * 384 + (k & 1) * 2 + 192);
  }
  wg_commit();
}
template <int kChains = 2>
__device__ __forceinline__ uint32_t sumsq(const uint32_t* z) {
  if (kChains == 1) {
    uint32_t a = h2mul(z[0], z[0]), b = h2mul(z[1], z[1]);
#pragma unroll
    for (int j = 1; j < 12; j++) { a = h2fma(z[2 * j], z[2 * j], a); b = h2fma(z[2 * j + 1], z[2 * j + 1], b); }
    return fold_add(a, b);
  }
  uint32_t q0[2], q1[2];
#pragma unroll
  for (int j = 0; j < 12; j++) {
    const uint32_t u = z[2 * j], v = z[2 * j + 1];
    q0[j & 1] = j < 2 ? h2mul(u, u) : h2fma(u, u, q0[j & 1]); q1[j & 1] = j < 2 ? h2mul(v, v) : h2fma(v, v, q1[j & 1]);
  }
  return fold_add(h2add(q0[0], q0[1]), h2add(q1[0], q1[1]));
}
__device__ __forceinline__ uint32_t rowsum(const uint32_t* z) {
  uint32_t a[2], b[2];
#pragma unroll
  for (int r = 0; r < 2; r++) {
    a[r] = h2add(h2add(h2add(z[r], z[r + 2]), h2add(z[r + 4], z[r + 6])), h2add(z[r + 8], z[r + 10]));
    b[r] = h2add(h2add(h2add(z[r + 12], z[r + 14]), h2add(z[r + 16], z[r + 18])), h2add(z[r + 20], z[r + 22]));
  }
  return fold_add(h2add(a[0], b[0]), h2add(a[1], b[1]));
}
__device__ __forceinline__ void scores_e(uint32_t* e, const uint32_t* q, const uint32_t* z) {
  uint32_t d[4];
#pragma unroll
  for (int j = 0; j < 12; j++) {
#pragma unroll
    for (int k = 0; k < 4; k++) d[k] = j ? h2fma(q[2 * j + (k >> 1)], z[2 * j + (k & 1)], d[k]) : h2mul(q[k >> 1], z[k & 1]);
  }
  e[0] = fold_add(d[0], d[2]); e[1] = fold_add(d[1], d[3]);
}
__device__ __forceinline__ uint32_t scores_r(const uint32_t* e, uint32_t selK) {
  return h2add(prmt(e[0], e[1], selK), __shfl_xor_sync(0xffffffffu, prmt(e[0], e[1], selK ^ 0x2222u), 1));
}
__device__ __forceinline__ uint32_t scores(const uint32_t* q, const uint32_t* z, uint32_t selK) {
  uint32_t e[2];
  scores_e(e, q, z);
  return scores_r(e, selK);
}
__device__ __forceinline__ float2 rstd(float2 d) { return make_float2(rsq_fast(fmaf(d.x, 1.f / 96.f, 1e-5f)), rsq_fast(fmaf(d.y, 1.f / 96.f, 1e-5f))); }
__device__ __forceinline__ void ln1_f32(uint32_t* z, const A3& la, int t, float* ie, float* m) {
  float acc[48];
  uint32_t x0[12], x1[12];
  load_row(x0, la, t); load_row(x1, la, t + 1);
#pragma unroll
  for (int j = 0; j < 12; j++) {
    acc[4 * j] = __uint_as_float(x0[j] << 16); acc[4 * j + 1] = __uint_as_float(x0[j] & 0xffff0000u);
    acc[4 * j + 2] = __uint_as_float(x1[j] << 16); acc[4 * j + 3] = __uint_as_float(x1[j] & 0xffff0000u);
  }
  float s[4], q[4];
#pragma unroll
  for (int e = 0; e < 4; e++) { s[e] = acc[e]; q[e] = acc[e] * acc[e]; }
#pragma unroll
  for (int j = 4; j < 48; j++) { s[j & 3] += acc[j]; q[j & 3] = fmaf(acc[j], acc[j], q[j & 3]); }
  const float s0 = quad_sum(s[0] + s[1]), s1 = quad_sum(s[2] + s[3]), q0 = quad_sum(q[0] + q[1]), q1 = quad_sum(q[2] + q[3]);
  const float u0 = rsq_fast(fmaxf(fmaf(-s0, s0, fmaf(q0, 96.f, kEps96)), kEps96));
  const float u1 = rsq_fast(fmaxf(fmaf(-s1, s1, fmaf(q1, 96.f, kEps96)), kEps96));
  const float n0 = -s0 * u0, n1 = -s1 * u1;
  ie[0] = 96.f * u0; ie[1] = 96.f * u1;
  m[0] = s0 * (1.f / 96.f); m[1] = s1 * (1.f / 96.f);
#pragma unroll
  for (int j = 0; j < 12; j++) {
    const int e = 4 * (j & ~1) + (j & 1);
    z[2 * j] = pack_h2(fmaf(acc[e], ie[0], n0), fmaf(acc[e + 4], ie[0], n0));
    z[2 * j + 1] = pack_h2(fmaf(acc[e + 2], ie[1], n1), fmaf(acc[e + 6], ie[1], n1));
  }
}
__device__ __forceinline__ float2 sumsq_f32(const uint32_t* z) {
  float2 qq = make_float2(0.f, 0.f);
#pragma unroll
  for (int j = 0; j < 12; j++) {
    const float2 u = unpack_h2(z[2 * j]), v = unpack_h2(z[2 * j + 1]);
    qq.x = fmaf(u.x, u.x, fmaf(u.y, u.y, qq.x)); qq.y = fmaf(v.x, v.x, fmaf(v.y, v.y, qq.y));
  }
  return make_float2(quad_sum(qq.x), quad_sum(qq.y));
}
__device__ __forceinline__ float2 var96_f32(const uint32_t* z, uint32_t my) {
  const float2 q = sumsq_f32(z), m = unpack_h2(my);
  return make_float2(fmaf(-96.f * m.x, m.x, q.x), fmaf(-96.f * m.y, m.y, q.y));
}
__device__ __forceinline__ void ln2(uint32_t* h, uint32_t rr, uint32_t my, const A3& ma, int t) {
  const uint32_t nn = as_u(__hmul2(__hneg2(as_h2(my)), as_h2(rr)));
#pragma unroll
  for (int j = 0; j < 12; j++) { h[2 * j] = h2fma(h[2 * j], lo2(rr), lo2(nn)); h[2 * j + 1] = h2fma(h[2 * j + 1], hi2(rr), hi2(nn)); }
#pragma unroll
  for (int k = 0; k < 3; k++) { stsm4(ma.a[k] + t * kFrame, h + 8 * k); stsm4((ma.a[k] ^ 32) + t * kFrame, h + 8 * k + 4); }
}

__device__ __forceinline__ uint32_t ring_pos(uint32_t r) { return min(r, r - 196u); }
__device__ __forceinline__ uint32_t ring_row(uint32_t r) { return ((r * 1338u) >> 16) * (kBufStride - kChunk) + r * 64; }
__device__ __forceinline__ uint32_t ring_stat(uint32_t r) { return ((r * 1338u) >> 16) * (kBufStride - 49 * 4) + r * 4; }
__device__ __forceinline__ A3 t_in_addr(uint32_t sb, uint32_t r0, int lane) {
  return swz3(sb + kOffBuf + (lane & 3) * 16 + ring_row(ring_pos(r0 + (lane >> 2))));
}
__device__ __forceinline__ A3 t_out_addr(uint32_t sb, uint32_t r0, int lane) {
  return swz3(sb + kOffBuf + ((lane >> 3) & 1) * kFrame + (lane & 16) + ring_row(ring_pos(r0 + (lane & 7))));
}
__device__ __forceinline__ uint32_t t_stat_addr(uint32_t sb, uint32_t r0, int lane) {
  return sb + kOffBuf + kXBytes + (lane & 3) * kFrame + ring_stat(ring_pos(r0 + (lane >> 2)));
}
__device__ __forceinline__ void t_release(uint32_t bar, uint32_t ia, uint32_t ib, int lane) {
  __syncwarp();
  asm volatile("{\n.reg .pred p;\nsetp.le.u32 p, %1, %2;\n@p mbarrier.arrive.shared::cta.b64 _, [%0];\n}"
               ::"r"(bar + ((ia + lane) & 3) * 8), "r"(lane), "r"(ib - ia) : "memory");
}
template <bool kDirect>
__device__ __forceinline__ void softmax4(uint32_t* s, uint32_t rhoA, uint32_t rhoB, uint32_t ro, float f) {
  if (kDirect) { s[0] = h2mul(s[0], rhoA); s[1] = h2mul(s[1], rhoB); }
  uint32_t mx = h2max(s[0], s[1]);
  mx = h2max(lo2(mx), hi2(mx));
  if (kDirect) {
    const uint32_t nm = as_u(__hmul2(__hneg2(as_h2(mx)), as_h2(ro)));
    s[0] = h2fma(s[0], ro, nm); s[1] = h2fma(s[1], ro, nm);
  } else {
    s[0] = h2mul(h2sub(s[0], mx), ro); s[1] = h2mul(h2sub(s[1], mx), ro);
  }
  s[0] = h2ex2(s[0]); s[1] = h2ex2(s[1]);
  uint32_t sm = h2add(s[0], s[1]);
  sm = h2add(lo2(sm), hi2(sm));
  const float iv = f * rcp_fast(__low2float(as_h2(sm)));
  const uint32_t inv = pack_h2(iv, iv);
  if (kDirect) { s[0] = h2mul(h2mul(s[0], rhoA), inv); s[1] = h2mul(h2mul(s[1], rhoB), inv); }
  else { s[0] = h2mul(s[0], inv); s[1] = h2mul(s[1], inv); }
}
template <bool kFirst>
__device__ __forceinline__ void mix(uint32_t* u, const uint32_t* z, uint32_t p0, uint32_t p1) {
#pragma unroll
  for (int j = 0; j < 12; j++) {
    u[2 * j] = h2fma(z[2 * j + 1], hi2(p0), kFirst ? h2mul(z[2 * j], lo2(p0)) : h2fma(z[2 * j], lo2(p0), u[2 * j]));
    u[2 * j + 1] = h2fma(z[2 * j + 1], hi2(p1), kFirst ? h2mul(z[2 * j], lo2(p1)) : h2fma(z[2 * j], lo2(p1), u[2 * j + 1]));
  }
}
template <bool kDirect>
__device__ __forceinline__ void put_stats(uint32_t sa, float sg, float mm, const Params& P) {
  const bool ok = (sg >= P.sgmin) & (kDirect || fmaf(sg, 9.8f, fabsf(mm)) < fmaf(P.kappa, -627.2f, 60000.f));
  const uint32_t sh = pack_h2(sg, mm), sw = pack_bf2(-sg, mm);
  asm volatile("st.shared.b32 [%0], %1;" ::"r"(sa), "r"(ok ? sh : sw) : "memory");
}

__device__ __forceinline__ bool task_T(uint32_t sb, uint32_t r0, uint32_t ia, uint32_t ib, uint32_t flag, int lane, const Params& P TRARG) {
  TR(1);
  const int c = lane & 3;
  const uint32_t selK = (c & 1) ? 0x7632u : 0x5410u, selO = 0x1010u + c * 0x2222u;
  const uint64_t da = mk_desc(sb, 1), dw = mk_desc(sb + kOffWt, 1);
  uint32_t x[48], yA[24], yB[24], qA[26], qB[26], ssA, ssB;
  {
    const A3 la = t_in_addr(sb, r0, lane);
#pragma unroll
    for (int t = 0; t < 4; t++) load_row(x + 12 * t, la, t);
  }
  row_to_h2(yA, x); row_to_h2(yA + 1, x + 12);
  TR(2);
  row_to_h2(yB, x + 24); row_to_h2(yB + 1, x + 36);
  ssB = sumsq<C1>(yB);
  ssA = sumsq<C1>(yA);
  if (SPL & 1) gemm_at2(qA, yA, da); else gemm_at(qA, yA, da);
  if (SPL & 2) gemm_at2(qB, yB, da); else gemm_at(qB, yB, da);
  TR(3);
  ssB = quad_h2add(ssB);
  ssA = quad_h2add(ssA);
  uint32_t rA[2], rB[2];
  wg_wait<1>(); pin<26>(qA);
  TR(4);
  const uint32_t myA = __byte_perm(qA[24], qA[25], 0x5410), nuA = __byte_perm(qA[24], qA[25], 0x7632);
  const uint32_t nsA = h2mul(myA, 0xd600d600u);
  const float2 ra = rstd(unpack_h2(h2fma(nsA, myA, ssA)));
  const uint32_t rhoA = pack_h2(ra.x, ra.y);
  rA[0] = scores(qA, yA, selK);
  if (HD & 2) { hold(sb, rA[0]); hold(sb, rhoA); } else sched_fence(rA[0], rhoA, 0);
  wg_wait<0>(); pin<26>(qB);
  TR(5);
  const uint32_t myB = __byte_perm(qB[24], qB[25], 0x5410), nuB = __byte_perm(qB[24], qB[25], 0x7632);
  const uint32_t nsB = h2mul(myB, 0xd600d600u);
  const float2 rb = rstd(unpack_h2(h2fma(nsB, myB, ssB)));
  const uint32_t rhoB = pack_h2(rb.x, rb.y);
  const uint32_t ro = prmt(rhoA, rhoB, selO), mo = bitsel(prmt(myA, myB, selO), 0xffffu, 0x292e0000u);
  asm volatile("{\n.reg .pred p, q;\n.reg .b32 t;\nabs.f16x2 t, %1;\nsetp.gtu.f16x2 p|q, t, %2;\nor.pred p, p, q;\n@p st.volatile.shared.b32 [%0], %2;\n}"
               ::"r"(flag), "r"(h2fma(ro, mo, 0xbc190000u)), "r"(0x3c003c00u) : "memory");
  uint32_t mu;
  rA[1] = scores(qA, yB, selK); rB[0] = scores(qB, yA, selK); rB[1] = scores(qB, yB, selK);
  uint32_t p[8], s[2];
#pragma unroll
  for (int k = 0; k < 2; k++) s[k] = h2add((c & 2) ? rB[k] : rA[k], __shfl_xor_sync(0xffffffffu, (c & 2) ? rA[k] : rB[k], 2));
  softmax4<true>(s, rhoA, rhoB, ro, P.kt);
#pragma unroll
  for (int t = 0; t < 4; t++) { p[2 * t] = __shfl_sync(0xffffffffu, s[0], t, 4); p[2 * t + 1] = __shfl_sync(0xffffffffu, s[1], t, 4); }
  mu = h2fma(s[1], nuB, h2mul(s[0], nuA));
  mix<true>(qA, yA, p[0], p[2]); mix<false>(qA, yB, p[1], p[3]);
  mu = h2add(lo2(mu), hi2(mu));
  mix<true>(qB, yA, p[4], p[6]);
  TR(6);
  if (SPL & 4) gemm_w2(yA, qA, dw); else gemm_w<1>(yA, qA, dw);
  sched_fence(0, 0, 0);
  mix<false>(qB, yB, p[5], p[7]);
  if (SPL & 8) gemm_w2(yB, qB, dw); else gemm_w<1>(yB, qB, dw);
  const A3 ma = t_out_addr(sb, r0, lane);
  if (HD & 4) hold(sb, ma.a[0] ^ ma.a[1] ^ ma.a[2]);
  TR(7);
  wg_wait<1>(); pin<24>(yA);
  TR(8);
  uint32_t bad;
  asm volatile("ld.shared.b32 %0, [%1];" : "=r"(bad) : "r"(flag + (yA[0] & (gridDim.x == 0x7fffffffu))) : "memory");
  float2 d = unpack_h2(h2fma(nsA, myA, quad_h2add(sumsq<C2>(yA))));
  if (UNLIKELY(__any_sync(0xffffffffu, !(d.x + d.y < 65000.f) | (bad != 0)))) {
    if (__any_sync(0xffffffffu, bad != 0)) {
      wg_wait<0>(); pin<24>(yB);
      return false;
    }
    d = var96_f32(yA, myA);
  }
  float2 r = rstd(make_float2(fabsf(d.x), fabsf(d.y)));
  const uint32_t rrA = pack_h2(r.x, r.y);
  ln2(yA, rrA, myA, ma, 0);
  if (DA) t_release(sb + kOffBar + 32, ia, ib, lane);
  wg_wait<0>(); pin<24>(yB);
  TR(9);
  d = unpack_h2(h2fma(nsB, myB, quad_h2add(sumsq<C2>(yB))));
  if (UNLIKELY(__any_sync(0xffffffffu, !(d.x + d.y < 65000.f)))) d = var96_f32(yB, myB);
  r = rstd(make_float2(fabsf(d.x), fabsf(d.y)));
  const uint32_t rrB = pack_h2(r.x, r.y);
  ln2(yB, rrB, myB, ma, 2);
  put_stats<true>(t_stat_addr(sb, r0, lane), rcp_fast(__low2float(as_h2(prmt(rrA, rrB, selO)))), __low2float(as_h2(CM ? prmt(myA, myB, selO) : h2add(mo, mu))), P);
  return true;
}

__device__ __forceinline__ void task_T_general(uint32_t sb, uint32_t r0, const Params& P) {
  int lane;
  asm volatile("mov.u32 %0, %%laneid;" : "=r"(lane));
  const int c = lane & 3;
  const uint64_t da = mk_desc(sb, 1), dw = mk_desc(sb + kOffWt, 1);
  uint32_t yA[24], yB[24], qA[26], qB[26];
  float ieo, mo, ao;
  {
    float ie[4], m[4];
    const A3 la = t_in_addr(sb, r0, lane);
    ln1_f32(yA, la, 0, ie, m);
    ln1_f32(yB, la, 2, ie + 2, m + 2);
    const float2 na = sumsq_f32(yA), nb = sumsq_f32(yB);
    const float ik = 9.8f * rcp_fast(P.kt) * rsq_fast(fmaxf(fmaxf(fmaxf(na.x, na.y), fmaxf(nb.x, nb.y)), 2e-7f));
    ieo = (c & 2) ? ((c & 1) ? ie[3] : ie[2]) : ((c & 1) ? ie[1] : ie[0]);
    mo = (c & 2) ? ((c & 1) ? m[3] : m[2]) : ((c & 1) ? m[1] : m[0]);
    const bool lim = (ieo * P.kt > 400.f) & (ik < ieo);
    const float u = ik * rcp_fast(ieo);
    ao = lim ? u : 1.f; ieo = lim ? ik : ieo;
  }
  uint32_t rA[2], rB[2], s[2], p[8];
  const uint32_t selK = (c & 1) ? 0x7632u : 0x5410u;
  gemm_at(qA, yA, da);
  wg_wait<0>(); pin<26>(qA);
  const uint32_t nuA = __byte_perm(qA[24], qA[25], 0x7632);
  rA[0] = scores(qA, yA, selK); rA[1] = scores(qA, yB, selK);
  sched_fence(rA[0], rA[1], nuA);
  gemm_at(qB, yB, da);
  wg_wait<0>(); pin<26>(qB);
  const uint32_t nuB = __byte_perm(qB[24], qB[25], 0x7632);
  rB[0] = scores(qB, yA, selK); rB[1] = scores(qB, yB, selK);
#pragma unroll
  for (int k = 0; k < 2; k++) s[k] = h2add((c & 2) ? rB[k] : rA[k], __shfl_xor_sync(0xffffffffu, (c & 2) ? rA[k] : rB[k], 2));
  softmax4<false>(s, 0, 0, score_scale(&g_par.cS_t), P.kt * ieo);
  uint32_t mu = h2fma(s[1], nuB, h2mul(s[0], nuA));
  mu = h2add(lo2(mu), hi2(mu));
#pragma unroll
  for (int t = 0; t < 4; t++) { p[2 * t] = __shfl_sync(0xffffffffu, s[0], t, 4); p[2 * t + 1] = __shfl_sync(0xffffffffu, s[1], t, 4); }
  sched_fence(mu, 0, 0);
  mix<true>(qA, yA, p[0], p[2]); mix<false>(qA, yB, p[1], p[3]);
  mix<true>(qB, yA, p[4], p[6]); mix<false>(qB, yB, p[5], p[7]);
  const uint32_t ah = pack_h2(ao, ao);
#pragma unroll
  for (int t = 0; t < 4; t++) {
    const uint32_t a = __shfl_sync(0xffffffffu, ah, t, 4);
#pragma unroll
    for (int j = 0; j < 12; j++) asm volatile("mul.f16x2 %0, %0, %1;" : "+r"(((t & 2) ? yB : yA)[2 * j + (t & 1)]) : "r"(a));
  }
  gemm_w<1>(yA, qA, dw);
  gemm_w<1>(yB, qB, dw);
  wg_wait<0>(); pin<24>(yA); pin<24>(yB);
  asm volatile("mov.u32 %0, %%laneid;" : "=r"(lane));
  float ie[4];
#pragma unroll
  for (int t = 0; t < 4; t++) ie[t] = __shfl_sync(0xffffffffu, ieo, t, 4);
  const float2 da2 = sumsq_f32(yA), db2 = sumsq_f32(yB);
  const uint32_t rrA = pack_h2_sat(rsq_fast(fmaf(da2.x, 1.f / 96.f, 1e-5f * ie[0] * ie[0])), rsq_fast(fmaf(da2.y, 1.f / 96.f, 1e-5f * ie[1] * ie[1])));
  const uint32_t rrB = pack_h2_sat(rsq_fast(fmaf(db2.x, 1.f / 96.f, 1e-5f * ie[2] * ie[2])), rsq_fast(fmaf(db2.y, 1.f / 96.f, 1e-5f * ie[3] * ie[3])));
  const A3 ma = t_out_addr(sb, r0, lane);
  ln2(yA, rrA, 0u, ma, 0); ln2(yB, rrB, 0u, ma, 2);
  const float r = __low2float(as_h2(prmt(rrA, rrB, 0x1010u + (lane & 3) * 0x2222u))), sg = rcp_fast(r * ieo);
  put_stats<false>(t_stat_addr(sb, r0, lane), sg, fmaf(__low2float(as_h2(mu)) * r, sg, mo), P);
}

__device__ __forceinline__ void claim(uint32_t sb, uint32_t nfull) {
  const uint32_t nb = gridDim.x, nrem = kNWIN - nfull * nb;
  const uint32_t whole = max((int)(nrem * NWH / 49), (int)(2 * nrem - nb));
  uint32_t t = blockIdx.x;
  if (DYN) asm volatile("atom.relaxed.gpu.global.inc.u32 %0, [%1], 0x7fffffff;" : "=r"(t) : "l"(&g_ctr) : "memory");
  const uint32_t u = t - whole;
  sts32(sb + kOffClaim, t < whole ? (nfull * nb + t) | 0x10000u
                        : u < 2 * (nrem - whole) ? (nfull * nb + whole + (u >> 1)) | 0x50000u | ((u & 1) << 17)
                        : blockIdx.x + (nfull - 1) * nb);
}
__device__ __forceinline__ void loop_T(uint32_t sb, int nfull, int wg, int wp, int lane, const Params& P, bool direct TRARG) {
  const uint32_t barF = sb + kOffBar, barD = sb + (DA ? kOffBarB : kOffBar + 32), flag = sb + kOffFlag + wg * 4;
  mbar_wait(sb + kOffBarW, 0);
  uint32_t r0 = 32 * wg + 8 * wp, par = 0;
  int k = (49 * nfull + 63 - 32 * wg) >> 6;
  int kx = ((49 * nfull + 112 - 32 * wg) >> 6) - k;
  int kc = wg + wp ? 0 : k - ((49 * (nfull - 3) - 1) >> 6);
  for (;;) {
    TR(0);
    if (UNLIKELY(k <= kc)) {
      if (k) {
        if (lane == 0) claim(sb, nfull);
        __syncwarp();
        kc = 0;
      } else {
        mbar_wait(barF + (nfull & 3) * 8, (nfull >> 2) & 1);
        k = __any_sync(0xffffffffu, lds32(sb + kOffClaim) & 0x10000u) ? kx : 0;
        kx = 0;
        if (k == 0) break;
      }
    }
    k--;
    const uint32_t ia = (r0 * 1338u) >> 16, ib = ((r0 + 7) * 1338u) >> 16;
    mbar_wait(barF + ia * 8, par);
    if (UNLIKELY(ib != ia)) mbar_wait(barF + (ib & 3) * 8, par ^ (ib >> 2));
    const uint32_t r = r0;
    r0 += 64;
    if (r0 >= 196) { r0 -= 196; par ^= 1; }
    if (LIKELY(direct)) {
      if (LIKELY(task_T(sb, r, ia, ib, flag, lane, P TRPASS(trp)))) {
        t_release(barD, ia, ib, lane);
        continue;
      }
      asm volatile("barrier.cta.sync.aligned %0, 128;" ::"r"(wg + 1) : "memory");
      asm volatile("st.shared.b32 [%0], %1;\nfence.acq_rel.cta;" ::"r"(flag), "r"(0) : "memory");
    }
    task_T_general(sb, r, P);
    if (DA) t_release(sb + kOffBar + 32, ia, ib, lane);
    t_release(barD, ia, ib, lane);
  }
}

struct SFrame {
  uint32_t oo;
  uint32_t t;
  uint32_t st;
  uint32_t d;
  bool light;
};
__device__ __forceinline__ SFrame s_frame(uint32_t sb, int t, int wp, int lane, A3& ma) {
  SFrame f;
  const int rb = (wp + t) & 3;
  f.light = rb == 3;
  f.t = t;
  f.d = ((sb + kOffBuf + t * kFrame) >> 4) & 0x3fff;
  f.st = t * kFrame + kXBytes + rb * 64;
  ma = swz3(t * kFrame + rb * 1024 + ((lane * 65) & 0x3d0));
  if (f.light && (lane & 15)) ma.a[0] = ma.a[1] = ma.a[2] = kXBytes + 256;
  const uint32_t r = 16 * rb + (lane >> 2);
  f.oo = (r + (r / 7) * (kW - 7)) * 12 + (lane & 3) + (((r + 8 + ((r + 8) / 7) * (kW - 7)) * 12 + (lane & 3)) << 16);
  asm volatile("" : "+r"(f.oo));
  return f;
}
template <int kRow>
__device__ __forceinline__ uint8_t* out_row(uint8_t* ob, const SFrame& f) {
  uint32_t o = f.oo;
  asm volatile("" : "+r"(o));
  uint8_t* r;
  asm("mad.wide.u32 %0, %1, 16, %2;" : "=l"(r) : "r"(kRow ? o >> 16 : o & 0xffffu), "l"(ob));
  return r;
}
template <int kHi>
__device__ __forceinline__ void s_load(uint32_t (&v)[24], uint32_t buf, A3 ma) {
  asm volatile("" : "+r"(ma.a[0]), "+r"(ma.a[1]), "+r"(ma.a[2]));
#pragma unroll
  for (int k = 0; k < 3; k++) {
    const uint32_t a = kHi ? ma.a[k] >> 16 : ma.a[k] & 0xffffu;
    ldsm4(v + 8 * k, buf + a); ldsm4(v + 8 * k + 4, buf + (a ^ 32));
  }
}
__device__ __forceinline__ void gemm_s(uint32_t* s, const uint32_t* q, uint64_t dA) {
  wg_fence();
  wg56h<0>(s, q, dA); wg56h<1>(s, q + 4, dA + 2);
  wg56h<1>(s, q + 8, dA + 196); wg56h<1>(s, q + 12, dA + 198);
  wg56h<1>(s, q + 16, dA + 392); wg56h<1>(s, q + 20, dA + 394);
  wg_commit();
}
template <bool kAll>
__device__ __forceinline__ void stg128(uint8_t* o, const uint32_t* w, uint32_t doit) {
  if (kAll) asm volatile("st.global.v4.b32 [%0], {%1,%2,%3,%4};" ::"l"(o), "r"(w[0]), "r"(w[1]), "r"(w[2]), "r"(w[3]) : "memory");
  else asm volatile("{\n.reg .pred p;\nsetp.ne.u32 p, %5, 0x7bff;\n@p st.global.v4.b32 [%0], {%1,%2,%3,%4};\n}" ::"l"(o), "r"(w[0]), "r"(w[1]), "r"(w[2]), "r"(w[3]), "r"(doit) : "memory");
}
template <int kRow, bool kAll>
__device__ __forceinline__ void s_store(const uint32_t (&v)[24], uint32_t e, uint8_t* o) {
  uint32_t w[12];
#pragma unroll
  for (int j = 0; j < 12; j += 2) {
    const float2 y = unpack_h2(h2fma(v[2 * j + kRow], lo2(e), hi2(e))), z = unpack_h2(h2fma(v[2 * j + 2 + kRow], lo2(e), hi2(e)));
    w[j] = pack_bf2(y.x, z.x); w[j + 1] = pack_bf2(y.y, z.y);
  }
#pragma unroll
  for (int i3 = 0; i3 < 3; i3++) stg128<kAll>(o + 64 * i3, w + 4 * i3, e);
}
template <int kRow, bool kAdd>
__device__ __forceinline__ void s_store_wide(const uint32_t (&v)[24], uint32_t e, uint8_t* o, const Params& P) {
  const float2 z = stat_f32(e);
#pragma unroll
  for (int i3 = 0; i3 < 3; i3++) {
    uint32_t w[4] = {0, 0, 0, 0};
    if (kAdd)
      asm volatile("{\n.reg .pred p;\nsetp.ne.u32 p, %5, 0x7bff;\n@p ld.global.v4.b32 {%0,%1,%2,%3}, [%4];\n}"
                   : "+r"(w[0]), "+r"(w[1]), "+r"(w[2]), "+r"(w[3]) : "l"(o + 64 * i3), "r"(e) : "memory");
#pragma unroll
    for (int j = 0; j < 4; j++) {
      const float2 ya = unpack_h2(v[8 * i3 + 2 * (j & 2) + kRow]), yb = unpack_h2(v[8 * i3 + 2 * (j & 2) + 2 + kRow]);
      const float2 y = (j & 1) ? make_float2(ya.y, yb.y) : make_float2(ya.x, yb.x);
      w[j] = kAdd ? pack_bf2(fmaf(y.x, P.kappa, __uint_as_float(w[j] << 16)), fmaf(y.y, P.kappa, __uint_as_float(w[j] & 0xffff0000u)))
                  : pack_bf2(fmaf(y.x, z.x, z.y), fmaf(y.y, z.x, z.y));
    }
    stg128<false>(o + 64 * i3, w, e);
  }
  __syncwarp();
}
__device__ __forceinline__ uint32_t ex2_pair(uint32_t s, uint32_t sel) {
  uint32_t lo, hi;
  asm volatile("{\n.reg .b16 a, b, c;\nmov.b32 {a, b}, %2;\nex2.approx.f16 c, a;\ncvt.u32.u16 %0, c;\nex2.approx.f16 c, b;\ncvt.u32.u16 %1, c;\n}"
               : "=r"(lo), "=r"(hi) : "r"(s));
  return QP ? prmt(lo, hi, sel) : lo + hi * 65536u;
}
__device__ __forceinline__ uint32_t ex2_lo(uint32_t s) {
  uint32_t lo;
  asm volatile("{\n.reg .b16 a, b, c;\nmov.b32 {a, b}, %1;\nex2.approx.f16 c, a;\ncvt.u32.u16 %0, c;\n}" : "=r"(lo) : "r"(s));
  return lo;
}

__device__ __forceinline__ void turn_wait(uint32_t j) { asm volatile("barrier.cta.sync.aligned %0, 256;" ::"r"(5 + j) : "memory"); }
__device__ __forceinline__ void turn_pass(uint32_t j) { asm volatile("barrier.cta.arrive.aligned %0, 256;" ::"r"(6 - j) : "memory"); }

template <int kSecond>
__device__ __forceinline__ void step_S(uint32_t sb, uint32_t (&v)[24], uint32_t (&vn)[24], uint32_t (&q)[24], uint32_t (&s)[16], const SFrame& f,
                                       const SFrame& fn, const A3& ma, uint32_t i, uint32_t nfull, uint32_t w4, uint32_t& cl, uint8_t* ob, int lane, const Params& P,
                                       bool scaled, const CUtensorMap* tm TRARG) {
  TR(0);
  const uint32_t ia = i & 3, ib = kSecond ? (i + 1) & 3 : ia;
  const uint32_t buf = sb + kOffBuf + ia * kBufStride, bufn = sb + kOffBuf + ib * kBufStride;
  const uint32_t never = gridDim.x == 0x7fffffffu;
  const uint64_t dQ0 = mk_desc(sb + kOffAs, 1), dQ = (HQ & 1) ? dQ0 : dQ0 + ((i + kSecond) & never), dW = ((HQ & 2) ? dQ0 : dQ0 + ((i + kSecond) & never)) + (kWMat >> 4);
  uint32_t p[16], u[24], e0, e1;
  ob += f.t * (kH * kW * 192u);
  const uint32_t nw = nfull + ((cl >> 16) & 1);
  asm volatile("" : "+l"(ob));
  uint32_t g4 = lane;
  asm volatile("" : "+r"(g4));
  uint32_t stu = buf + f.st;
  asm volatile("" : "+r"(stu));
  const uint32_t sta = stu + (g4 & 0x1c);
  asm volatile("ld.shared.b32 %0, [%1];" : "=r"(e0) : "r"(sta) : "memory");
  asm volatile("ld.shared.b32 %0, [%1];" : "=r"(e1) : "r"(sta + 32) : "memory");
  const uint32_t keep = (lane & 3) == 0 ? 0x0000ffffu : 0u;
  const bool pad0 = QP && f.light && lane >= 4, pad1 = QP && f.light;
  const uint32_t sel0 = pad0 ? 0x3232u : 0x5410u, sel1 = pad1 ? 0x3232u : 0x5410u;
  s[12] = bitsel(s[12], QP == 1 && pad0 ? 0u : keep, 0xfc00fc00u); s[13] = bitsel(s[13], QP == 1 && pad1 ? 0u : keep, 0xfc00fc00u);
  const uint32_t x0 = h2max(h2max(h2max(h2max(s[0], s[2]), s[4]), h2max(h2max(s[6], s[8]), s[10])), s[12]);
  const uint32_t x1 = h2max(h2max(h2max(h2max(s[1], s[3]), s[5]), h2max(h2max(s[7], s[9]), s[11])), s[13]);
  const bool ok = __hble2(__hmax2(__habs2(as_h2(x0)), __habs2(as_h2(x1))), as_h2(0x47004700u)) & !scaled;
  constexpr int kE = IL == 0 ? 12 : IL == 1 ? 4 : IL == 2 ? 0 : 8;
  p[12] = ex2_lo(s[12]); p[13] = ex2_lo(s[13]);
  if (QP == 3) { p[12] = prmt(p[12], 0, sel0); p[13] = prmt(p[13], 0, sel1); }
#pragma unroll
  for (int j = 0; j < kE; j++) p[j] = ex2_pair(s[j], (j & 1) ? sel1 : sel0);
  if (UNLIKELY(!__all_sync(0xffffffffu, ok))) {
    uint32_t mx = h2max(__byte_perm(x0, x1, 0x5410), __byte_perm(x0, x1, 0x7632));
    mx = h2max(mx, __shfl_xor_sync(0xffffffffu, mx, 1));
    mx = h2max(mx, __shfl_xor_sync(0xffffffffu, mx, 2));
    const uint32_t cs = lds32(sb + kOffCs);
#pragma unroll
    for (int j = 0; j < 7; j++) { s[2 * j] = h2mul(h2sub(s[2 * j], lo2(mx)), cs); s[2 * j + 1] = h2mul(h2sub(s[2 * j + 1], hi2(mx)), cs); }
    p[12] = ex2_lo(s[12]); p[13] = ex2_lo(s[13]);
  if (QP == 3) { p[12] = prmt(p[12], 0, sel0); p[13] = prmt(p[13], 0, sel1); }
#pragma unroll
    for (int j = 0; j < kE; j++) p[j] = ex2_pair(s[j], (j & 1) ? sel1 : sel0);
  }
  asm volatile("mov.b32 %0, 0;\nmov.b32 %1, 0;" : "=r"(p[14]), "=r"(p[15]));
  TR(1);
  const uint64_t mn = OB ? desc_at(f.d + ia * (kBufStride >> 4) + (kChunk >> 4 << 16)) : mk_desc(buf + f.t * kFrame, kChunk >> 4);
  wg_fence();
  wg96h<2, 1>(q, p + 12, mn + 192, never); wg96h<1, 1>(q, p, mn);
#pragma unroll
  for (int j = 4; j < 12; j++) p[j] = ex2_pair(s[j], (j & 1) ? sel1 : sel0);
  const bool wide = __any_sync(0xffffffffu, ((e0 | e1) & 0x8000u) != 0u);
  uint32_t rs = fold_add(h2add(h2add(h2add(p[0], p[2]), p[12]), h2add(h2add(p[4], p[6]), h2add(p[8], p[10]))),
                         h2add(h2add(h2add(p[1], p[3]), p[13]), h2add(h2add(p[5], p[7]), h2add(p[9], p[11])))), rt;
  asm volatile("shfl.sync.bfly.b32 %0, %1, 1, 31, 0xffffffff;" : "=r"(rt) : "r"(rs));
  wg_fence();
  wg96h<1, 1>(q, p + 4, mn + 64); wg96h<1, 1>(q, p + 8, mn + 128);
  wg_commit();
  TR(2);
  float g0 = __low2float(as_h2(e0)), g1 = __low2float(as_h2(e1));
  if (UNLIKELY(wide)) {
    s_store_wide<0, false>(v, e0, out_row<0>(ob, f), P); s_store_wide<1, false>(v, e1, out_row<1>(ob, f), P);
    asm volatile("mov.b32 %0, %2;\nmov.b32 %1, %2;" : "=f"(g0), "=f"(g1) : "f"(P.kappa));
  }
  rs = h2add(rs, rt);
  asm volatile("shfl.sync.bfly.b32 %0, %1, 2, 31, 0xffffffff;" : "=r"(rt) : "r"(rs));
  auto next = [&]() {
    if (i + 1 < nw) mbar_wait(sb + kOffBar + 32 + ib * 8, ((i + 1) >> 2) & 1);
    s_load<0>(vn, bufn, ma);
  };
  if (!kSecond) s_load<1>(vn, bufn, ma);
  else if (LD == 1) next();
  else if (LD == 3) s_load<0>(vn, bufn, ma);
  rs = h2add(rs, rt);
  const float d0 = __low2float(as_h2(rs)), d1 = __high2float(as_h2(rs));
  const float c0 = P.kappa * rcp_fast(d0 * g0), c1 = P.kappa * rcp_fast(d1 * g1);
  const uint32_t cb = OA == 3 ? pack_h2_sat(c0, c1) : OA == 2 ? pack_h2_rz(c0, c1) : OA ? pack_h2(c0, c1) : pack_h2(e0 != kPadStat ? c0 : 0.f, e1 != kPadStat ? c1 : 0.f);
  if (HD & 1) hold(sb, cb);
  if (PG == 1) turn_wait(f.t & 1);
  wg_wait<0>(); pin<24>(q);
  TR(3);
  if (PG == 2) turn_wait(f.t & 1);

  if (kSecond && LD == 2) next();
  auto refill = [&]() {
    if (EL) {
      if (f.light & (i + 4 <= nw)) {
        const uint32_t c = i + 4 >= nfull ? cl : w4;
        tma_load_elect<!kSecond>(buf + f.t * kFrame, tm, sb + kOffBar + ia * 8, c & 0xffffu, f.t ^ ((c >> 16) & 2), fn.t ^ ((c >> 16) & 2));
      }
    } else if (f.light) {
      const uint32_t bar = sb + kOffBar + ia * 8;
      if (lane == 0) {
        const uint32_t c = i + 4 >= nfull ? cl : w4;
        if (i + 4 <= nw) {
          tma_load(buf + f.t * kFrame, tm, bar, c & 0xffffu, f.t ^ ((c >> 16) & 2));
          if (!kSecond) tma_prefetch(tm, c & 0xffffu, fn.t ^ ((c >> 16) & 2));
        }
      }
      __syncwarp();
    }
  };
#pragma unroll
  for (int j = 0; j < 12; j++) { u[2 * j] = h2mul(q[2 * j], lo2(cb)); u[2 * j + 1] = h2mul(q[2 * j + 1], hi2(cb)); }
  if (PG == 3) turn_wait(f.t & 1);
  TR(4);
  gemm_w<2>(v, u, dW, !wide);
  if (PG && PR == 0) turn_pass(f.t & 1);

  if (RF == 0 || ((RF == 1 || RF == 4) && kSecond)) refill();
  if (kSecond && LD == 0) next();
  gemm_w<2>(q, vn, dQ, never);
  if (RF == 2 || (RF == 1 && !kSecond)) refill();
  if (PG && PR == 1) turn_pass(f.t & 1);
  TR(5);
  if (OH && kSecond && i + 1 < nw) mbar_wait(sb + kOffBarB + ib * 8, ((i + 1) >> 2) & 1);
  if (kSecond && UNLIKELY(i + 5 == nfull)) cl = __shfl_sync(0xffffffffu, lds32(sb + kOffClaim), 0);
  const bool plain = !(wide | f.light);
  wg_wait<1>(); pin<24>(v);
  if (kSecond || !OH) asm volatile("fence.proxy.async.shared::cta;" ::: "memory");
  if (PG && PR == 2) turn_pass(f.t & 1);
  TR(6);
  if (LIKELY(plain)) s_store<0, true>(v, e0, out_row<0>(ob, f));
  else if (RF == 3 || (RF == 4 && !kSecond)) refill();
  if (PG && PR == 3) turn_pass(f.t & 1);
  wg_wait<0>(); pin<24>(q);
  TR(7);
  gemm_s(s, q, OB ? desc_at(fn.d + ib * (kBufStride >> 4) + (1 << 16)) : mk_desc(bufn + fn.t * kFrame, 1));
  if (PG && PR == 4) turn_pass(f.t & 1);

  if (LIKELY(plain)) s_store<1, true>(v, e1, out_row<1>(ob, f));
  else if (!wide) { s_store<0, false>(v, e0, out_row<0>(ob, f)); __syncwarp(); }
  else if (wide) { s_store_wide<0, true>(v, e0, out_row<0>(ob, f), P); s_store_wide<1, true>(v, e1, out_row<1>(ob, f), P); }
  if (PG && PR == 5) turn_pass(f.t & 1);
  if (!OH && kSecond && i + 1 < nw) mbar_wait(sb + kOffBarB + ib * 8, ((i + 1) >> 2) & 1);
  wg_wait<0>(); pin<14>(s);
}

__device__ __forceinline__ void loop_S(uint32_t sb, uint32_t nfull, int t0, int wp, int lane, const Params& P, bool scaled,
                                       const CUtensorMap* tm, uint8_t* __restrict__ out TRARG) {
  A3 ma, mb;
  const SFrame f0 = s_frame(sb, t0, wp, lane, ma), f1 = s_frame(sb, t0 + 2, wp, lane, mb);
#pragma unroll
  for (int k = 0; k < 3; k++) ma.a[k] += mb.a[k] << 16;
  uint32_t v0[24], v1[24], q[24], s[16];
  sts32(sb + kOffCs, pack_h2(P.cS_s, P.cS_s));
  mbar_wait(sb + kOffBarW + 8, 0);
  mbar_wait(sb + kOffBar + 32, 0);
  s_load<0>(v0, sb + kOffBuf, ma);
  gemm_w<0>(q, v0, mk_desc(sb + kOffAs, 1));
  if (OH) mbar_wait(sb + kOffBarB, 0);
  asm volatile("fence.proxy.async.shared::cta;" ::: "memory");
  wg_wait<0>(); pin<24>(q);
  gemm_s(s, q, mk_desc(sb + kOffBuf + f0.t * kFrame, 1));
  if (DA) mbar_wait(sb + kOffBarB, 0);
  wg_wait<0>(); pin<14>(s);
  if (PG && t0 == PF0) turn_pass(t0);
  uint32_t cl = 0, w0 = blockIdx.x;
  for (uint32_t i = 0;; i++, w0 += gridDim.x) {
    const bool more = i + 1 < nfull + ((cl >> 16) & 1);
    const uint32_t c = i == nfull ? cl : w0, w = c & 0xffffu;
    const uint32_t wy = (w * 57457u) >> 22;
    uint8_t* ob = out + (size_t)((wy * (7 * kW - 7 * kNWX) + w * 7 + ((c >> 16) & 2) * (kH * kW)) * 192u);
    asm volatile("" : "+l"(ob));
    step_S<0>(sb, v0, v1, q, s, f0, f1, ma, i, nfull, w0 + 4 * gridDim.x, cl, ob, lane, P, scaled, tm TRPASS(trp + 16 * i));
    if (c & 0x40000u) break;
    step_S<1>(sb, v1, v0, q, s, f1, f0, ma, i, nfull, w0 + 4 * gridDim.x, cl, ob, lane, P, scaled, tm TRPASS(trp + 16 * i + 8));
    if (!more) break;
  }
  if (PG && t0 != PF0) turn_wait(t0);
  const uint32_t nw = nfull + ((cl >> 16) & 1);
  mbar_wait(sb + kOffBar + (nw & 3) * 8, (nw >> 2) & 1);
}

__global__ void __launch_bounds__(LB, 1) swin_main(const __grid_constant__ Maps maps, uint8_t* __restrict__ out) {
  const CUtensorMap& tm = maps.tm;
  extern __shared__ __align__(1024) uint8_t smem[];
  const uint32_t sb = smem_u32(smem);
  const int tid = threadIdx.x;
  const int wg = __shfl_sync(0xffffffffu, tid >> 7, 0);
  const int wp = __shfl_sync(0xffffffffu, (tid >> 5) & 3, 0);
  const int lane = tid & 31;
  const int b = blockIdx.x, nb = gridDim.x;
  const int nfull = kNWIN / nb;
  if (tid == 0) {
    if ((sb & 1023) || nfull < 8) __trap();
#pragma unroll
    for (int i = 0; i < 4; i++) {
      mbar_init(sb + kOffBar + i * 8, 4);
      mbar_init(sb + kOffBar + 32 + i * 8, 7);
      mbar_init(sb + kOffBarB + i * 8, 7);
    }
    asm volatile("st.shared.v4.b32 [%0], {%1,%1,%1,%1};" ::"r"(sb + kOffFlag), "r"(0) : "memory");
    mbar_init(sb + kOffBarW, 1); mbar_init(sb + kOffBarW + 8, 1);
    asm volatile("fence.mbarrier_init.release.cluster;" ::: "memory");
  }
  if (tid >= 128 && tid < 488) {
    const uint32_t e = tid - 128, fr = min(e / 20, 15u);
    asm volatile("st.shared.v4.b32 [%0], {%1,%1,%1,%1};" ::"r"(sb + kOffBuf + fr * kFrame + kXBytes + (e - fr * 20) * 16), "r"(e - fr * 20 < 16 ? kPadStat : 0u) : "memory");
    asm volatile("fence.proxy.async.shared::cta;" ::: "memory");
  }
#pragma unroll
  for (int i = 0; i < PAD; i++) sched_fence(tid + i, 0, 0);
  __syncthreads();
  if (lane == 0 && wg < 2) tma_load(sb + kOffBuf + (tid >> 5) * kFrame, &tm, sb + kOffBar + wg * 8, b + wg * nb, wp);
  __syncwarp();
  asm volatile("griddepcontrol.wait;" ::: "memory");
  if (tid == 0) {
    if (!(WF & 1)) asm volatile("fence.proxy.async.global;" ::: "memory");
#pragma unroll
    for (int i = 0; i < 2; i++) {
      const uint32_t o = i ? kOffAs : 0, n = i ? kWBytes - kOffAs : kOffAs, bar = sb + kOffBarW + 8 * i;
      mbar_expect(bar, n);
      asm volatile("cp.async.bulk.shared::cluster.global.mbarrier::complete_tx::bytes [%0], [%1], %2, [%3];"
                   ::"r"(sb + o), "l"(reinterpret_cast<const uint8_t*>(g_wimg) + o), "r"(n), "r"(bar) : "memory");
    }
  }
  __syncwarp();
  if (wg >= 2) {
    if (WS) mbar_wait(sb + kOffBarW + (WS == 2 || (WS == 3 && wg == 3) ? 8 : 0), 0);
    if (lane == 0) tma_load(sb + kOffBuf + (tid >> 5) * kFrame, &tm, sb + kOffBar + wg * 8, b + wg * nb, wp);
    __syncwarp();
  }
  Params P;
  {
    const float4 p0 = __ldcg(reinterpret_cast<const float4*>(&g_par));
    P.cS_t = p0.x; P.cS_s = p0.y; P.kt = p0.z; P.kappa = p0.w;
    P.sgmin = fmaxf(0.0045f, P.kappa * 0.011f);
  }
  const bool scaled = __any_sync(0xffffffffu, P.cS_s != 1.f);
  const bool direct = __all_sync(0xffffffffu, (P.cS_t == 1.f) & (P.kt <= 256.f) & (P.kappa <= 16.f));
  const int widx = __popc(((ROLE >> wg) & 1 ? ROLE : ~ROLE) & ((1 << wg) - 1));
  const bool isT = (ROLE >> wg) & 1;
  if (isT) {
    loop_T(sb, nfull, widx, wp, lane, P, direct TRPASS(g_trace + (b * 16 + wg * 4 + wp) * 1024));
  } else {
    loop_S(sb, nfull, widx, wp, lane, P, scaled, &tm, out TRPASS(g_trace + (b * 16 + wg * 4 + wp) * 1024));
  }
}

__device__ __forceinline__ int ch_pos(int ch) { return 32 * (ch >> 5) + 4 * (ch & 4) + 8 * (ch & 1) + 2 * ((ch >> 3) & 3) + ((ch >> 1) & 1); }
__device__ __forceinline__ float pow2_ceil(float v) {
  return __uint_as_float((__float_as_uint(v) + 0x7fffffu) & 0x7f800000u);
}

constexpr int kPrepSplit = 12;
constexpr int kPrepThreads = 384;
__global__ void __launch_bounds__(kPrepThreads) swin_prep(const __nv_bfloat16* __restrict__ wqkv_t, const __nv_bfloat16* __restrict__ wo_t,
                                                          const __nv_bfloat16* __restrict__ wqkv_s, const __nv_bfloat16* __restrict__ wo_s) {
  asm volatile("griddepcontrol.launch_dependents;");
  if (blockIdx.x == 0 && threadIdx.x == 0) g_ctr = 0;
  __shared__ __align__(16) uint32_t raw[2][96][52];
  __shared__ __align__(16) uint32_t mu[3][52];
  __shared__ float nrm[12], nrm2[6], csum[6][9];
  const int mat = blockIdx.x / kPrepSplit, blk = blockIdx.x % kPrepSplit;
  const int tid = threadIdx.x, lane = tid & 31, warp = tid >> 5, g = lane >> 2, c = lane & 3;
  const __nv_bfloat16* wqkv = mat < 2 ? wqkv_t : wqkv_s;
  const __nv_bfloat16* wo = mat < 2 ? wo_t : wo_s;
  const bool isA = (mat & 1) == 0;
  {
    uint4 v[3], u[3];
#pragma unroll
    for (int q = 0; q < 3; q++) {
      const int e = tid + q * kPrepThreads, i = e / 12, c8 = (e % 12) * 8;
      v[q] = __ldg(reinterpret_cast<const uint4*>(wqkv + i * 288 + (isA ? 0 : 192) + c8));
      u[q] = __ldg(reinterpret_cast<const uint4*>(isA ? wqkv + i * 288 + 96 + c8 : wo + i * 96 + c8));
    }
#pragma unroll
    for (int q = 0; q < 3; q++) {
      const int e = tid + q * kPrepThreads, i = e / 12, c4 = (e % 12) * 4;
      *reinterpret_cast<uint4*>(&raw[0][i][c4]) = v[q];
      *reinterpret_cast<uint4*>(&raw[1][i][c4]) = u[q];
    }
  }
  __syncthreads();
  {
    const int m = warp / 6, cp = (warp % 6) * 8 + g;
    float s0 = 0.f, s1 = 0.f, q0 = 0.f, q1 = 0.f;
#pragma unroll
    for (int i = 0; i < 24; i++) {
      const uint32_t w = raw[m][4 * i + c][cp];
      const float lo = __uint_as_float(w << 16), hi = __uint_as_float(w & 0xffff0000u);
      s0 += lo; s1 += hi; q0 = fmaf(lo, lo, q0); q1 = fmaf(hi, hi, q1);
    }
    s0 = quad_sum(s0) * (1.f / 96.f); s1 = quad_sum(s1) * (1.f / 96.f); q0 = quad_sum(q0); q1 = quad_sum(q1);
    if (mat == 1 && m == 1) {
      float r0 = 0.f, r1 = 0.f;
#pragma unroll
      for (int i = 0; i < 12; i++) {
        const uint32_t w0 = raw[1][2 * cp][4 * i + c], w1 = raw[1][2 * cp + 1][4 * i + c];
        r0 += __uint_as_float(w0 << 16) + __uint_as_float(w0 & 0xffff0000u);
        r1 += __uint_as_float(w1 << 16) + __uint_as_float(w1 & 0xffff0000u);
      }
      r0 = quad_sum(r0) * (1.f / 96.f); r1 = quad_sum(r1) * (1.f / 96.f);
      s0 = r0; s1 = r1;
    }
    if (m == 1 && c == 0) {
      const uint32_t hi = mat == 3 ? 0u : pack_bf2(s0, s1);
      mu[0][cp] = hi;
      mu[1][cp] = mat == 3 ? 0u : pack_bf2(s0 - __uint_as_float(hi << 16), s1 - __uint_as_float(hi & 0xffff0000u));
      mu[2][cp] = 0u;
    }
    if (m == 0 || isA) {
      q0 = fmaxf(fmaf(-96.f * s0, s0, q0), 0.f) + q0 * 1e-6f;
      q1 = fmaxf(fmaf(-96.f * s1, s1, q1), 0.f) + q1 * 1e-6f;
    }
    const bool usemax = m == 1 && mat == 3;
    float t = usemax ? fmaxf(q0, q1) : q0 + q1;
#pragma unroll
    for (int o = 4; o < 32; o <<= 1) { const float z = __shfl_xor_sync(0xffffffffu, t, o); t = usemax ? fmaxf(t, z) : t + z; }
    if (lane == 0) nrm[warp] = t;
  }
  __syncthreads();
  if (warp >= 6) return;
  float d[4] = {0.f, 0.f, 0.f, 0.f}, e[4] = {0.f, 0.f, 0.f, 0.f}, v0, v1;
  {
    const uint32_t arow = smem_u32(&raw[0][16 * warp + (lane & 15)][(lane >> 4) * 4]);
    const uint32_t brow = isA ? smem_u32(&raw[1][blk * 8 + (lane & 7)][(lane >> 3) * 4]) : smem_u32(&raw[1][lane][blk * 4]);
    const uint32_t mrow = smem_u32(&mu[min(lane & 7, 2)][(lane >> 3) * 4]);
#pragma unroll
    for (int k2 = 0; k2 < 3; k2++) {
      uint32_t b[4], m[4];
      if (isA) ldsm4(b, brow + k2 * 64);
      else asm volatile("ldmatrix.sync.aligned.m8n8.x4.trans.shared.b16 {%0,%1,%2,%3}, [%4];"
                        : "=r"(b[0]), "=r"(b[1]), "=r"(b[2]), "=r"(b[3]) : "r"(brow + k2 * (32 * 208)) : "memory");
      ldsm4(m, mrow + k2 * 64);
#pragma unroll
      for (int hf = 0; hf < 2; hf++) {
        uint32_t a[4];
        ldsm4(a, arow + (2 * k2 + hf) * 32);
        asm volatile("mma.sync.aligned.m16n8k16.row.col.f32.bf16.bf16.f32 {%0,%1,%2,%3},{%4,%5,%6,%7},{%8,%9},{%0,%1,%2,%3};"
                     : "+f"(d[0]), "+f"(d[1]), "+f"(d[2]), "+f"(d[3])
                     : "r"(a[0]), "r"(a[1]), "r"(a[2]), "r"(a[3]), "r"(b[2 * hf]), "r"(b[2 * hf + 1]));
        asm volatile("mma.sync.aligned.m16n8k16.row.col.f32.bf16.bf16.f32 {%0,%1,%2,%3},{%4,%5,%6,%7},{%8,%9},{%0,%1,%2,%3};"
                     : "+f"(e[0]), "+f"(e[1]), "+f"(e[2]), "+f"(e[3])
                     : "r"(a[0]), "r"(a[1]), "r"(a[2]), "r"(a[3]), "r"(m[2 * hf]), "r"(m[2 * hf + 1]));
      }
    }
    v0 = __shfl_sync(0xffffffffu, e[0] + e[1], lane & ~3); v1 = __shfl_sync(0xffffffffu, e[2] + e[3], lane & ~3);
    d[0] -= v0; d[1] -= v0; d[2] -= v1; d[3] -= v1;
    float t0 = d[0] + d[2], t1 = d[1] + d[3], t2 = v0 + v1;
#pragma unroll
    for (int o = 4; o < 32; o <<= 1) {
      t0 += __shfl_xor_sync(0xffffffffu, t0, o); t1 += __shfl_xor_sync(0xffffffffu, t1, o); t2 += __shfl_xor_sync(0xffffffffu, t2, o);
    }
    if (g == 0) { csum[warp][2 * c] = t0; csum[warp][2 * c + 1] = t1; csum[warp][8] = t2; }
  }
  const float nl = nrm[0] + nrm[1] + nrm[2] + nrm[3] + nrm[4] + nrm[5];
  const float nr = mat == 3 ? fmaxf(fmaxf(fmaxf(nrm[6], nrm[7]), fmaxf(nrm[8], nrm[9])), fmaxf(nrm[10], nrm[11]))
                            : nrm[6] + nrm[7] + nrm[8] + nrm[9] + nrm[10] + nrm[11];
  const float bound = __fsqrt_rn(nl) * __fsqrt_rn(nr) * 1.01f;
  const float f = isA ? 0.14724448f : 1.f;
  float sc = pow2_ceil(fmaxf(bound * (isA ? 0.14724448f / 160.f : mat == 1 ? 1.f / 16.f : 1.f / 64.f), 1e-30f));
  if (isA) sc = fminf(fmaxf(sc, 1.f), 32768.f);
  const float mul = f * __uint_as_float(0x7f000000u - __float_as_uint(sc));
  if (blk == 0 && tid == 0) (mat == 0 ? g_par.cS_t : mat == 1 ? g_par.kt : mat == 2 ? g_par.cS_s : g_par.kappa) = sc;
  asm volatile("bar.sync 1, 192;" ::: "memory");
  float mean[2];
#pragma unroll
  for (int b = 0; b < 2; b++)
    mean[b] = (csum[0][2 * c + b] + csum[1][2 * c + b] + csum[2][2 * c + b] + csum[3][2 * c + b] + csum[4][2 * c + b] + csum[5][2 * c + b]) *
              (1.f / 96.f);
  uint8_t* img = reinterpret_cast<uint8_t*>(g_wimg) + (mat == 0 ? 0 : mat == 1 ? kOffWt : mat == 2 ? kOffAs : kOffWs);
  const float vmean = (csum[0][8] + csum[1][8] + csum[2][8] + csum[3][8] + csum[4][8] + csum[5][8]) * (1.f / 96.f);
  float off = 0.f;
  if (mat == 2) {
    float q2 = 0.f;
#pragma unroll
    for (int q = 0; q < 4; q++) q2 = fmaf(d[q] - mean[q & 1], d[q] - mean[q & 1], q2);
#pragma unroll
    for (int o = 16; o; o >>= 1) q2 += __shfl_xor_sync(0xffffffffu, q2, o);
    if (lane == 0) nrm2[warp] = q2;
    asm volatile("bar.sync 1, 192;" ::: "memory");
    q2 = nrm2[0] + nrm2[1] + nrm2[2] + nrm2[3] + nrm2[4] + nrm2[5];
    off = 1.5f * pow2_ceil(fmaxf(__fsqrt_rn(q2 * (1.f / 768.f)) * mul * 3.f, 1e-4f));
  }
#pragma unroll
  for (int q = 0; q < 4; q++) {
    const int kp = ch_pos(16 * warp + g + 8 * (q >> 1)), np = ch_pos(blk * 8 + 2 * c + (q & 1));
    const uint32_t ko = (kp >> 5) * (mat == 0 ? kAtChunk : 6144) + (kp & 31) * 2;
    uint32_t a = ko + np * 64;
    a ^= ((a >> 7) & 3) << 4;
    float o = (d[q] - mean[q & 1]) * mul;
    o = mat == 2 ? o + off : __uint_as_float((__float_as_uint(o) + 0x8000u) & 0xffff0000u);
    *reinterpret_cast<__half*>(img + a) = __float2half_rn(o);
    if (mat == 1 && blk == 0) {
      a = (kp >> 5) * kAtChunk + (kp & 31) * 2 + (96 + 2 * c + (q & 1)) * 64;
      a ^= ((a >> 7) & 3) << 4;
      *reinterpret_cast<__half*>(reinterpret_cast<uint8_t*>(g_wimg) + a) = __float2half_rn((q & 1) ? ((q >> 1 ? v1 : v0) - vmean) * mul : 1.f / 96.f);
    }
  }
}

typedef CUresult (*EncodeFn)(CUtensorMap*, CUtensorMapDataType, cuuint32_t, void*, const cuuint64_t*, const cuuint64_t*,
                             const cuuint32_t*, const cuuint32_t*, CUtensorMapInterleave, CUtensorMapSwizzle,
                             CUtensorMapL2promotion, CUtensorMapFloatOOBfill);

}

extern "C" void kernel_launch(void* const* d_in, const int* in_sizes, int n_in, void* d_out, int out_size) {
  (void)in_sizes; (void)n_in; (void)out_size;
  static EncodeFn enc = nullptr;
  static int nsm = 0;
  if (!enc) {
    void* fn = nullptr;
    cudaDriverEntryPointQueryResult qr;
    cudaGetDriverEntryPoint("cuTensorMapEncodeTiled", &fn, cudaEnableDefault, &qr);
    enc = reinterpret_cast<EncodeFn>(fn);
    int dev = 0;
    cudaGetDevice(&dev);
    cudaDeviceGetAttribute(&nsm, cudaDevAttrMultiProcessorCount, dev);
    cudaFuncSetAttribute(swin_main, cudaFuncAttributeMaxDynamicSharedMemorySize, kSmemBytes);
  }
  Maps maps;
  CUtensorMap& tm = maps.tm;
  const cuuint64_t dims[5] = {32, kW, kH, kT, 3};
  const cuuint64_t strides[4] = {192, 192ull * kW, 192ull * kW * kH, 64};
  const cuuint32_t box[5] = {32, 7, 7, 1, 3};
  const cuuint32_t es[5] = {1, 1, 1, 1, 1};
  enc(&tm, CU_TENSOR_MAP_DATA_TYPE_BFLOAT16, 5, d_in[0], dims, strides, box, es, CU_TENSOR_MAP_INTERLEAVE_NONE,
      CU_TENSOR_MAP_SWIZZLE_64B, CU_TENSOR_MAP_L2_PROMOTION_L2_128B, CU_TENSOR_MAP_FLOAT_OOB_FILL_NONE);
  {
    const cuuint64_t d3[3] = {24 * kW, kH, kT};
    const cuuint64_t s3[2] = {192ull * kW, 192ull * kW * kH};
    const cuuint32_t b3[3] = {168, 7, 1};
    enc(&maps.pf, CU_TENSOR_MAP_DATA_TYPE_INT64, 3, d_in[0], d3, s3, b3, es, CU_TENSOR_MAP_INTERLEAVE_NONE,
        CU_TENSOR_MAP_SWIZZLE_NONE, (CUtensorMapL2promotion)PRM, CU_TENSOR_MAP_FLOAT_OOB_FILL_NONE);
  }

  cudaStream_t st = cudaStreamPerThread;
  swin_prep<<<4 * kPrepSplit, kPrepThreads, 0, st>>>(
      static_cast<const __nv_bfloat16*>(d_in[1]), static_cast<const __nv_bfloat16*>(d_in[2]),
      static_cast<const __nv_bfloat16*>(d_in[3]), static_cast<const __nv_bfloat16*>(d_in[4]));

  cudaLaunchConfig_t cfg = {};
  cfg.gridDim = dim3(nsm);
  cfg.blockDim = dim3(kNWG * 128);
  cfg.dynamicSmemBytes = kSmemBytes;
  cfg.stream = st;
  cudaLaunchAttribute at[1];
  at[0].id = cudaLaunchAttributeProgrammaticStreamSerialization;
  at[0].val.programmaticStreamSerializationAllowed = 1;
  cfg.attrs = at;
  cfg.numAttrs = 1;
  cudaLaunchKernelEx(&cfg, swin_main, maps, static_cast<uint8_t*>(d_out));
}
```

```cpp
#include <cuda_runtime.h>
#include <cuda.h>
#include <cuda_bf16.h>
#include <cuda_fp16.h>
#include <stdint.h>

#define LB 512
#define SF 17
#define TIE 0
#define SG 1
#define IL 1
#define FP 2
#define ROLE 3
#define RF 2
#define CK0 0
#define LIKELY(x) __builtin_expect(!!(x), 1)
#define UNLIKELY(x) __builtin_expect(!!(x), 0)
#define CV 1
#define C1 2
#define C2 2
#define WS 1
#define TL 1
#define PAD 0
#define SPL 1
#define SPN 64
#define SPO 1
#define LD 1
#define DA 1
#define E1 0
#define E2 0
#define E3 0
#define E4 0
#define G4 0
#define BE 0
#define CS 0
#define QP 3
#define PG 3
#define PR 4
#define PF0 1
#define EARLY 0
#define PF 2
#define HQ 0
#define PRM 2
#define CM 0
#define AB 0
#define ST 0
#define WF 0
#define NWH 25
#define DYN 1
#define EL 0
#define HD 0
#define OA 3
#define OB 1
#define OC 1
#define OH 1
#define XE 0
#define XP 0
#define XN 24
#define LP0 0
#define LP1 0
#define R1 1
#define SM 3
#define Q1 0
#define LA 4
#define LB2 4
#define LF 0
#define GB 0
#define GL 6
#define SQA 0
namespace {

constexpr int kH = 511, kW = 511, kT = 4;
constexpr int kNWX = 73, kNWIN = 73 * 73;
constexpr int kChunk = 3136;
constexpr int kXBytes = 3 * kChunk;
constexpr int kFrame = 9728;
constexpr int kBufStride = 4 * kFrame;
constexpr uint32_t kPadStat = 0x7bff;
constexpr int kWMat = 18432;
constexpr int kAtChunk = 104 * 64;
constexpr int kOffWt = 3 * kAtChunk;
constexpr int kOffAs = kOffWt + kWMat, kOffWs = kOffAs + kWMat;
constexpr int kWBytes = kOffWs + kWMat;
constexpr int kOffBuf = kWBytes;
constexpr int kOffBar = kOffBuf + 4 * kBufStride + 640;
constexpr int kOffFlag = kOffBar + 64;
constexpr int kOffBarW = kOffBar + 80;
constexpr int kOffBarB = kOffBar + 96;
constexpr int kOffCs = kOffBar + 128;
constexpr int kOffClaim = kOffBar + 132;
constexpr int kSmemBytes = kOffBar + 144;
constexpr int kNWG = 4;

struct Maps { CUtensorMap tm, pf; };
struct Params {
  float cS_t, cS_s;
  float kt;
  float kappa;
  float sgmin;
};

__device__ uint4 g_wimg[kWBytes / 16];
__device__ __align__(16) Params g_par;
__device__ uint32_t g_ctr;

#define TR(idx)
#define TRARG
#define TRPASS(x)
__device__ __forceinline__ uint32_t smem_u32(const void* p) { return (uint32_t)__cvta_generic_to_shared(p); }
__device__ __forceinline__ void mbar_init(uint32_t a, int c) { asm volatile("mbarrier.init.shared::cta.b64 [%0], %1;" ::"r"(a), "r"(c)); }
__device__ __forceinline__ void mbar_expect(uint32_t a, int bytes) {
  asm volatile("mbarrier.arrive.expect_tx.shared::cta.b64 _, [%0], %1;" ::"r"(a), "r"(bytes) : "memory");
}
__device__ __forceinline__ void mbar_arrive(uint32_t a) {
  asm volatile("mbarrier.arrive.shared::cta.b64 _, [%0];" ::"r"(a) : "memory");
}
__device__ __forceinline__ void mbar_wait(uint32_t a, uint32_t par) {
  asm volatile(
      "{\n.reg .pred p;\n.reg .u32 n;\n"
      "mbarrier.try_wait.parity.shared::cta.b64 p, [%0], %1;\n"
      "@p bra.uni WDONE;\n"
      "mov.u32 n, 0;\n"
      "WLOOP:\n"
      "mbarrier.try_wait.parity.shared::cta.b64 p, [%0], %1;\n"
      "@p bra.uni WDONE;\n"
      "add.u32 n, n, 1;\n"
      "setp.lt.u32 p, n, 0x1000000;\n"
      "@p bra.uni WLOOP;\n"
      "trap;\n"
      "WDONE:\n}" ::"r"(a), "r"(par) : "memory");
}
__device__ __forceinline__ void tma_load(uint32_t dst, const CUtensorMap* m, uint32_t bar, uint32_t w, uint32_t t) {
  const uint32_t wy = (w * 57457u) >> 22, wx = w - wy * kNWX;
  mbar_expect(bar, kXBytes);
  asm volatile(
      "cp.async.bulk.tensor.5d.shared::cluster.global.mbarrier::complete_tx::bytes [%0], [%1, {%3,%4,%5,%6,%3}], [%2];" ::"r"(dst),
      "l"(m), "r"(bar), "r"(0), "r"(wx * 7), "r"(wy * 7), "r"(t)
      : "memory");
}
__device__ __forceinline__ void tma_prefetch(const CUtensorMap* m, uint32_t w, uint32_t t) {
  const uint32_t wy = (w * 57457u) >> 22, wx = w - wy * kNWX;
  asm volatile("cp.async.bulk.prefetch.tensor.3d.L2.global [%0, {%1,%2,%3}];" ::"l"(m + 1), "r"(wx * 168), "r"(wy * 7), "r"(t) : "memory");
}
template <bool kPrefetch>
__device__ __forceinline__ void tma_load_elect(uint32_t dst, const CUtensorMap* m, uint32_t bar, uint32_t w, uint32_t t, uint32_t tp) {
  const uint32_t wy = (w * 57457u) >> 22, wx = w - wy * kNWX;
  asm volatile("{\n.reg .pred p;\nelect.sync _|p, 0xffffffff;\n"
               "@p mbarrier.arrive.expect_tx.shared::cta.b64 _, [%2], %7;\n"
               "@p cp.async.bulk.tensor.5d.shared::cluster.global.mbarrier::complete_tx::bytes [%0], [%1, {%3,%4,%5,%6,%3}], [%2];\n}"
               ::"r"(dst), "l"(m), "r"(bar), "r"(0), "r"(wx * 7), "r"(wy * 7), "r"(t), "n"(kXBytes) : "memory");
  if (kPrefetch)
    asm volatile("{\n.reg .pred p;\nelect.sync _|p, 0xffffffff;\n@p cp.async.bulk.prefetch.tensor.3d.L2.global [%0, {%1,%2,%3}];\n}"
                 ::"l"(m + 1), "r"(wx * 168), "r"(wy * 7), "r"(tp) : "memory");
}
__device__ __forceinline__ void wg_fence() { asm volatile("wgmma.fence.sync.aligned;" ::: "memory"); }
__device__ __forceinline__ void wg_commit() { asm volatile("wgmma.commit_group.sync.aligned;" ::: "memory"); }
template <int N>
__device__ __forceinline__ void wg_wait() { asm volatile("wgmma.wait_group.sync.aligned %0;" ::"n"(N) : "memory"); }
template <int N>
__device__ __forceinline__ void pin(uint32_t* d) {
#pragma unroll
  for (int i = 0; i < N; i++) asm volatile("" : "+r"(d[i])::"memory");
}
__device__ __forceinline__ void sched_fence(uint32_t a, uint32_t b, uint32_t c) {
  asm volatile("{\n.reg .pred p;\n.reg .b32 t;\nsetp.ne.u32 p, %0, 0x7fffffff;\n@p bra.uni SFD;\n"
               "add.u32 t, %1, %2;\nadd.u32 t, t, %3;\nnanosleep.u32 t;\nSFD:\n}" ::"r"(gridDim.x), "r"(a), "r"(b), "r"(c) : "memory");
}
__device__ __forceinline__ void hold(uint32_t sb, uint32_t v) {
  asm volatile("{\n.reg .pred p;\nsetp.eq.u32 p, %0, 0x7fffffff;\n@p st.volatile.shared.b32 [%1], %2;\n}" ::"r"(gridDim.x), "r"(sb), "r"(v) : "memory");
}
__device__ __forceinline__ uint64_t mk_desc(uint32_t addr, uint32_t lbo16) {
  return ((uint64_t)0x80000020u << 32) | ((addr >> 4) & 0x3fff) | (lbo16 << 16);
}

__device__ __forceinline__ uint64_t desc_at(uint32_t lo) { return ((uint64_t)0x80000020u << 32) | lo; }

#define R4(d, i) "+r"(d[i]), "+r"(d[i + 1]), "+r"(d[i + 2]), "+r"(d[i + 3])
#define O4(d, i) "=r"(d[i]), "=r"(d[i + 1]), "=r"(d[i + 2]), "=r"(d[i + 3])
#define D24 "{%0,%1,%2,%3,%4,%5,%6,%7,%8,%9,%10,%11,%12,%13,%14,%15,%16,%17,%18,%19,%20,%21,%22,%23},"
#define D14 "{%0,%1,%2,%3,%4,%5,%6,%7,%8,%9,%10,%11,%12,%13},"

template <int SC, int TB>
__device__ __forceinline__ void wg96h(uint32_t (&d)[24], const uint32_t* a, uint64_t db, uint32_t acc = 0) {
  if (SC == 2)
    asm volatile("{\n.reg .pred p;\nsetp.ne.u32 p, %30, 0;\n"
                 "wgmma.mma_async.sync.aligned.m64n96k16.f16.f16.f16 " D24 "{%24,%25,%26,%27}, %28, p, 1, 1, %29;\n}"
                 : R4(d, 0), R4(d, 4), R4(d, 8), R4(d, 12), R4(d, 16), R4(d, 20)
                 : "r"(a[0]), "r"(a[1]), "r"(a[2]), "r"(a[3]), "l"(db), "n"(TB), "r"(acc));
  else if (SC)
    asm volatile("wgmma.mma_async.sync.aligned.m64n96k16.f16.f16.f16 " D24 "{%24,%25,%26,%27}, %28, 1, 1, 1, %29;"
                 : R4(d, 0), R4(d, 4), R4(d, 8), R4(d, 12), R4(d, 16), R4(d, 20)
                 : "r"(a[0]), "r"(a[1]), "r"(a[2]), "r"(a[3]), "l"(db), "n"(TB));
  else
    asm volatile("wgmma.mma_async.sync.aligned.m64n96k16.f16.f16.f16 " D24 "{%24,%25,%26,%27}, %28, 0, 1, 1, %29;"
                 : O4(d, 0), O4(d, 4), O4(d, 8), O4(d, 12), O4(d, 16), O4(d, 20)
                 : "r"(a[0]), "r"(a[1]), "r"(a[2]), "r"(a[3]), "l"(db), "n"(TB));
}
template <int SC>
__device__ __forceinline__ void wg104h(uint32_t (&d)[26], const uint32_t* a, uint64_t db) {
  if (SC)
    asm volatile("wgmma.mma_async.sync.aligned.m64n104k16.f16.f16.f16 "
                 "{%0,%1,%2,%3,%4,%5,%6,%7,%8,%9,%10,%11,%12,%13,%14,%15,%16,%17,%18,%19,%20,%21,%22,%23,%24,%25},"
                 "{%26,%27,%28,%29}, %30, 1, 1, 1, 0;"
                 : R4(d, 0), R4(d, 4), R4(d, 8), R4(d, 12), R4(d, 16), R4(d, 20), "+r"(d[24]), "+r"(d[25])
                 : "r"(a[0]), "r"(a[1]), "r"(a[2]), "r"(a[3]), "l"(db));
  else
    asm volatile("wgmma.mma_async.sync.aligned.m64n104k16.f16.f16.f16 "
                 "{%0,%1,%2,%3,%4,%5,%6,%7,%8,%9,%10,%11,%12,%13,%14,%15,%16,%17,%18,%19,%20,%21,%22,%23,%24,%25},"
                 "{%26,%27,%28,%29}, %30, 0, 1, 1, 0;"
                 : O4(d, 0), O4(d, 4), O4(d, 8), O4(d, 12), O4(d, 16), O4(d, 20), "=r"(d[24]), "=r"(d[25])
                 : "r"(a[0]), "r"(a[1]), "r"(a[2]), "r"(a[3]), "l"(db));
}
template <int SC>
__device__ __forceinline__ void wg56h(uint32_t* d, const uint32_t* a, uint64_t db) {
  if (SC)
    asm volatile("wgmma.mma_async.sync.aligned.m64n56k16.f16.f16.f16 " D14 "{%14,%15,%16,%17}, %18, 1, 1, 1, 0;"
                 : R4(d, 0), R4(d, 4), R4(d, 8), "+r"(d[12]), "+r"(d[13])
                 : "r"(a[0]), "r"(a[1]), "r"(a[2]), "r"(a[3]), "l"(db));
  else
    asm volatile("wgmma.mma_async.sync.aligned.m64n56k16.f16.f16.f16 " D14 "{%14,%15,%16,%17}, %18, 0, 1, 1, 0;"
                 : O4(d, 0), O4(d, 4), O4(d, 8), "=r"(d[12]), "=r"(d[13])
                 : "r"(a[0]), "r"(a[1]), "r"(a[2]), "r"(a[3]), "l"(db));
}
template <int SC>
__device__ __forceinline__ void gemm_w(uint32_t (&d)[24], const uint32_t* a, uint64_t dw, uint32_t acc = 0) {
  wg_fence();
  wg96h<SC, 0>(d, a, dw, acc); wg96h<1, 0>(d, a + 4, dw + 2);
  wg96h<1, 0>(d, a + 8, dw + 384); wg96h<1, 0>(d, a + 12, dw + 386);
  wg96h<1, 0>(d, a + 16, dw + 768); wg96h<1, 0>(d, a + 20, dw + 770);
  wg_commit();
}
__device__ __forceinline__ void lds128(uint32_t* r, uint32_t a) {
  asm volatile("ld.shared.v4.b32 {%0,%1,%2,%3}, [%4];" : "=r"(r[0]), "=r"(r[1]), "=r"(r[2]), "=r"(r[3]) : "r"(a) : "memory");
}
__device__ __forceinline__ uint32_t lds32(uint32_t a) {
  uint32_t r; asm volatile("ld.volatile.shared.b32 %0, [%1];" : "=r"(r) : "r"(a) : "memory"); return r;
}
__device__ __forceinline__ void sts32(uint32_t a, uint32_t v) { asm volatile("st.volatile.shared.b32 [%0], %1;" ::"r"(a), "r"(v) : "memory"); }
__device__ __forceinline__ void ldsm4(uint32_t* r, uint32_t a) {
  asm volatile("ldmatrix.sync.aligned.m8n8.x4.shared.b16 {%0,%1,%2,%3}, [%4];"
               : "=r"(r[0]), "=r"(r[1]), "=r"(r[2]), "=r"(r[3]) : "r"(a) : "memory");
}
__device__ __forceinline__ void stsm4(uint32_t a, const uint32_t* r) {
  asm volatile("stmatrix.sync.aligned.m8n8.x4.shared.b16 [%0], {%1,%2,%3,%4};" ::"r"(a), "r"(r[0]), "r"(r[1]), "r"(r[2]), "r"(r[3])
               : "memory");
}
__device__ __forceinline__ uint32_t pack_h2(float lo, float hi) {
  uint32_t r; asm("cvt.rn.f16x2.f32 %0, %1, %2;" : "=r"(r) : "f"(hi), "f"(lo)); return r;
}
__device__ __forceinline__ uint32_t pack_h2_rz(float lo, float hi) {
  uint32_t r; asm("cvt.rz.f16x2.f32 %0, %1, %2;" : "=r"(r) : "f"(hi), "f"(lo)); return r;
}
__device__ __forceinline__ uint32_t pack_h2_sat(float lo, float hi) {
  uint32_t r; asm("cvt.rn.satfinite.f16x2.f32 %0, %1, %2;" : "=r"(r) : "f"(hi), "f"(lo)); return r;
}
__device__ __forceinline__ uint32_t pack_bf2(float lo, float hi) {
  uint32_t r; asm("cvt.rn.bf16x2.f32 %0, %1, %2;" : "=r"(r) : "f"(hi), "f"(lo)); return r;
}
__device__ __forceinline__ __half2 as_h2(uint32_t v) { return *reinterpret_cast<__half2*>(&v); }
__device__ __forceinline__ uint32_t as_u(__half2 v) { return *reinterpret_cast<uint32_t*>(&v); }
__device__ __forceinline__ float2 unpack_h2(uint32_t v) { return __half22float2(as_h2(v)); }
__device__ __forceinline__ uint32_t h2ex2(uint32_t v) { uint32_t r; asm("ex2.approx.f16x2 %0, %1;" : "=r"(r) : "r"(v)); return r; }
__device__ __forceinline__ uint32_t h2max(uint32_t a, uint32_t b) { return as_u(__hmax2(as_h2(a), as_h2(b))); }
__device__ __forceinline__ uint32_t h2add(uint32_t a, uint32_t b) { return as_u(__hadd2(as_h2(a), as_h2(b))); }
__device__ __forceinline__ uint32_t h2sub(uint32_t a, uint32_t b) { return as_u(__hsub2(as_h2(a), as_h2(b))); }
__device__ __forceinline__ uint32_t h2mul(uint32_t a, uint32_t b) { return as_u(__hmul2(as_h2(a), as_h2(b))); }
__device__ __forceinline__ uint32_t h2fma(uint32_t a, uint32_t b, uint32_t c) { return as_u(__hfma2(as_h2(a), as_h2(b), as_h2(c))); }
__device__ __forceinline__ uint32_t lo2(uint32_t v) { return as_u(__low2half2(as_h2(v))); }
__device__ __forceinline__ uint32_t hi2(uint32_t v) { return as_u(__high2half2(as_h2(v))); }
__device__ __forceinline__ uint32_t fold_add(uint32_t a, uint32_t b) { return h2add(__byte_perm(a, b, 0x5410), __byte_perm(a, b, 0x7632)); }
__device__ __forceinline__ uint32_t bitsel(uint32_t a, uint32_t m, uint32_t c) {
  uint32_t r; asm("lop3.b32 %0, %1, %2, %3, 0xe2;" : "=r"(r) : "r"(a), "r"(m), "r"(c)); return r;
}
__device__ __forceinline__ float rcp_fast(float v) { float r; asm("rcp.approx.ftz.f32 %0, %1;" : "=f"(r) : "f"(v)); return r; }
__device__ __forceinline__ float rsq_fast(float v) { float r; asm("rsqrt.approx.ftz.f32 %0, %1;" : "=f"(r) : "f"(v)); return r; }
__device__ __forceinline__ float quad_sum(float v) {
  v += __shfl_xor_sync(0xffffffffu, v, 1);
  return v + __shfl_xor_sync(0xffffffffu, v, 2);
}
__device__ __forceinline__ uint32_t quad_h2add(uint32_t v) {
  if (Q1) return h2add(h2add(v, __shfl_xor_sync(0xffffffffu, v, 1)), h2add(__shfl_xor_sync(0xffffffffu, v, 2), __shfl_xor_sync(0xffffffffu, v, 3)));
  v = h2add(v, __shfl_xor_sync(0xffffffffu, v, 1));
  return h2add(v, __shfl_xor_sync(0xffffffffu, v, 2));
}
__device__ __forceinline__ uint32_t score_scale(const float* p) { const float v = __ldcg(p); return pack_h2(v, v); }

constexpr float kEps96 = 1e-5f * 96.f * 96.f;
__device__ __forceinline__ float2 stat_f32(uint32_t e) {
  const float2 h = unpack_h2(e);
  return make_float2((e & 0x8000u) ? __uint_as_float((e << 16) & 0x7fff0000u) : h.x, (e & 0x8000u) ? __uint_as_float(e & 0xffff0000u) : h.y);
}

__device__ __forceinline__ uint32_t swz(uint32_t a) { return a ^ ((a >> 3) & 0x30); }
__device__ __forceinline__ uint32_t prmt(uint32_t a, uint32_t b, uint32_t s) {
  uint32_t r; asm("prmt.b32 %0, %1, %2, %3;" : "=r"(r) : "r"(a), "r"(b), "r"(s)); return r;
}
__device__ __forceinline__ void tie48(uint32_t* a, uint32_t* b, uint64_t d, uint32_t u = 0, uint32_t v = 0) {
  asm volatile("{\n.reg .pred p;\n.reg .b32 t;\nsetp.ne.u32 p, %48, 0x7fffffff;\n@p bra.uni TIED;\n"
               "wgmma.fence.sync.aligned;\n"
               "wgmma.mma_async.sync.aligned.m64n192k16.f16.f16.f16 {%0,%1,%2,%3,%4,%5,%6,%7,%8,%9,%10,%11,%12,%13,%14,%15,%16,%17,%18,%19,%20,%21,%22,%23,%24,%25,%26,%27,%28,%29,%30,%31,%32,%33,%34,%35,%36,%37,%38,%39,%40,%41,%42,%43,%44,%45,%46,%47}, %49, %49, 1, 1, 1, 0, 0;\n"
               "wgmma.commit_group.sync.aligned;\nwgmma.wait_group.sync.aligned 0;\nTIED:\n}"
               : R4(a, 0), R4(a, 4), R4(a, 8), R4(a, 12), R4(a, 16), R4(a, 20), R4(b, 0), R4(b, 4), R4(b, 8), R4(b, 12), R4(b, 16), R4(b, 20)
               : "r"(gridDim.x), "l"(d), "r"(u), "r"(v) : "memory");
}
template <int kPos>
__device__ __forceinline__ void x_work(uint32_t sb, uint32_t v) {
  if (XP != kPos) return;
  uint32_t a = v, b = v + 1, c = v + 2;
#pragma unroll
  for (int i = 0; i < XN / 3; i++)
    asm volatile("fma.rn.f16x2 %0, %0, %3, %3;\nfma.rn.f16x2 %1, %1, %3, %3;\nfma.rn.f16x2 %2, %2, %3, %3;" : "+r"(a), "+r"(b), "+r"(c) : "r"(v));
  hold(sb, a ^ b ^ c);
}
struct A3 { uint32_t a[3]; };
__device__ __forceinline__ A3 swz3(uint32_t a) { return A3{{swz(a), swz(a + kChunk), swz(a + 2 * kChunk)}}; }
__device__ __forceinline__ void load_row(uint32_t* x, const A3& a, int t) {
  lds128(x, a.a[0] + t * kFrame); lds128(x + 4, a.a[1] + t * kFrame); lds128(x + 8, a.a[2] + t * kFrame);
}
__device__ __forceinline__ void row_to_h2(uint32_t* y, const uint32_t* x) {
#pragma unroll
  for (int j = 0; j < 12; j += 2) {
    y[2 * j] = pack_h2(__uint_as_float(x[j] << 16), __uint_as_float(x[j + 1] << 16));
    uint32_t r;
    asm("cvt.rz.f16x2.f32 %0, %1, %2;" : "=r"(r) : "f"(__uint_as_float(x[j + 1])), "f"(__uint_as_float(x[j])));
    y[2 * j + 2] = r & 0xfff8fff8u;
  }
}
__device__ __forceinline__ void gemm_at(uint32_t (&q)[26], const uint32_t* z, uint64_t da) {
  wg_fence();
  wg104h<0>(q, z, da); wg104h<1>(q, z + 4, da + 2);
  wg104h<1>(q, z + 8, da + 416); wg104h<1>(q, z + 12, da + 418);
  wg104h<1>(q, z + 16, da + 832); wg104h<1>(q, z + 20, da + 834);
  wg_commit();
}
template <int SC>
__device__ __forceinline__ void wg64h(uint32_t* d, const uint32_t* a, uint64_t db) {
  if (SC)
    asm volatile("wgmma.mma_async.sync.aligned.m64n64k16.f16.f16.f16 {%0,%1,%2,%3,%4,%5,%6,%7,%8,%9,%10,%11,%12,%13,%14,%15}, {%16,%17,%18,%19}, %20, 1, 1, 1, 0;"
                 : "+r"(d[0]), "+r"(d[1]), "+r"(d[2]), "+r"(d[3]), "+r"(d[4]), "+r"(d[5]), "+r"(d[6]), "+r"(d[7]), "+r"(d[8]), "+r"(d[9]), "+r"(d[10]), "+r"(d[11]), "+r"(d[12]), "+r"(d[13]), "+r"(d[14]), "+r"(d[15])
                 : "r"(a[0]), "r"(a[1]), "r"(a[2]), "r"(a[3]), "l"(db));
  else
    asm volatile("wgmma.mma_async.sync.aligned.m64n64k16.f16.f16.f16 {%0,%1,%2,%3,%4,%5,%6,%7,%8,%9,%10,%11,%12,%13,%14,%15}, {%16,%17,%18,%19}, %20, 0, 1, 1, 0;"
                 : "=r"(d[0]), "=r"(d[1]), "=r"(d[2]), "=r"(d[3]), "=r"(d[4]), "=r"(d[5]), "=r"(d[6]), "=r"(d[7]), "=r"(d[8]), "=r"(d[9]), "=r"(d[10]), "=r"(d[11]), "=r"(d[12]), "=r"(d[13]), "=r"(d[14]), "=r"(d[15])
                 : "r"(a[0]), "r"(a[1]), "r"(a[2]), "r"(a[3]), "l"(db));
}
template <int SC>
__device__ __forceinline__ void wg40h(uint32_t* d, const uint32_t* a, uint64_t db) {
  if (SC)
    asm volatile("wgmma.mma_async.sync.aligned.m64n40k16.f16.f16.f16 {%0,%1,%2,%3,%4,%5,%6,%7,%8,%9}, {%10,%11,%12,%13}, %14, 1, 1, 1, 0;"
                 : "+r"(d[0]), "+r"(d[1]), "+r"(d[2]), "+r"(d[3]), "+r"(d[4]), "+r"(d[5]), "+r"(d[6]), "+r"(d[7]), "+r"(d[8]), "+r"(d[9])
                 : "r"(a[0]), "r"(a[1]), "r"(a[2]), "r"(a[3]), "l"(db));
  else
    asm volatile("wgmma.mma_async.sync.aligned.m64n40k16.f16.f16.f16 {%0,%1,%2,%3,%4,%5,%6,%7,%8,%9}, {%10,%11,%12,%13}, %14, 0, 1, 1, 0;"
                 : "=r"(d[0]), "=r"(d[1]), "=r"(d[2]), "=r"(d[3]), "=r"(d[4]), "=r"(d[5]), "=r"(d[6]), "=r"(d[7]), "=r"(d[8]), "=r"(d[9])
                 : "r"(a[0]), "r"(a[1]), "r"(a[2]), "r"(a[3]), "l"(db));
}
template <int SC>
__device__ __forceinline__ void wg80h(uint32_t* d, const uint32_t* a, uint64_t db) {
  if (SC)
    asm volatile("wgmma.mma_async.sync.aligned.m64n80k16.f16.f16.f16 {%0,%1,%2,%3,%4,%5,%6,%7,%8,%9,%10,%11,%12,%13,%14,%15,%16,%17,%18,%19}, {%20,%21,%22,%23}, %24, 1, 1, 1, 0;"
                 : "+r"(d[0]), "+r"(d[1]), "+r"(d[2]), "+r"(d[3]), "+r"(d[4]), "+r"(d[5]), "+r"(d[6]), "+r"(d[7]), "+r"(d[8]), "+r"(d[9]), "+r"(d[10]), "+r"(d[11]), "+r"(d[12]), "+r"(d[13]), "+r"(d[14]), "+r"(d[15]), "+r"(d[16]), "+r"(d[17]), "+r"(d[18]), "+r"(d[19])
                 : "r"(a[0]), "r"(a[1]), "r"(a[2]), "r"(a[3]), "l"(db));
  else
    asm volatile("wgmma.mma_async.sync.aligned.m64n80k16.f16.f16.f16 {%0,%1,%2,%3,%4,%5,%6,%7,%8,%9,%10,%11,%12,%13,%14,%15,%16,%17,%18,%19}, {%20,%21,%22,%23}, %24, 0, 1, 1, 0;"
                 : "=r"(d[0]), "=r"(d[1]), "=r"(d[2]), "=r"(d[3]), "=r"(d[4]), "=r"(d[5]), "=r"(d[6]), "=r"(d[7]), "=r"(d[8]), "=r"(d[9]), "=r"(d[10]), "=r"(d[11]), "=r"(d[12]), "=r"(d[13]), "=r"(d[14]), "=r"(d[15]), "=r"(d[16]), "=r"(d[17]), "=r"(d[18]), "=r"(d[19])
                 : "r"(a[0]), "r"(a[1]), "r"(a[2]), "r"(a[3]), "l"(db));
}
template <int SC>
__device__ __forceinline__ void wg24h(uint32_t* d, const uint32_t* a, uint64_t db) {
  if (SC)
    asm volatile("wgmma.mma_async.sync.aligned.m64n24k16.f16.f16.f16 {%0,%1,%2,%3,%4,%5}, {%6,%7,%8,%9}, %10, 1, 1, 1, 0;"
                 : "+r"(d[0]), "+r"(d[1]), "+r"(d[2]), "+r"(d[3]), "+r"(d[4]), "+r"(d[5])
                 : "r"(a[0]), "r"(a[1]), "r"(a[2]), "r"(a[3]), "l"(db));
  else
    asm volatile("wgmma.mma_async.sync.aligned.m64n24k16.f16.f16.f16 {%0,%1,%2,%3,%4,%5}, {%6,%7,%8,%9}, %10, 0, 1, 1, 0;"
                 : "=r"(d[0]), "=r"(d[1]), "=r"(d[2]), "=r"(d[3]), "=r"(d[4]), "=r"(d[5])
                 : "r"(a[0]), "r"(a[1]), "r"(a[2]), "r"(a[3]), "l"(db));
}
__device__ __forceinline__ void gemm_at2(uint32_t (&q)[26], const uint32_t* z, uint64_t da) {
  wg_fence();
#define WA wg64h
#define WB wg40h
  constexpr int o = SPN / 4, e = SPN * 4;
  WA<0>(q, z, da); WB<0>(q + o, z, da + e); WA<1>(q, z + 4, da + 2); WB<1>(q + o, z + 4, da + e + 2);
  WA<1>(q, z + 8, da + 416); WB<1>(q + o, z + 8, da + e + 416); WA<1>(q, z + 12, da + 418); WB<1>(q + o, z + 12, da + e + 418);
  WA<1>(q, z + 16, da + 832); WB<1>(q + o, z + 16, da + e + 832); WA<1>(q, z + 20, da + 834); WB<1>(q + o, z + 20, da + e + 834);
  wg_commit();
}
__device__ __forceinline__ void wg48h(uint32_t* d, const uint32_t* a, uint64_t db) {
  asm volatile("wgmma.mma_async.sync.aligned.m64n48k16.f16.f16.f16 {%0,%1,%2,%3,%4,%5,%6,%7,%8,%9,%10,%11}, {%12,%13,%14,%15}, %16, 1, 1, 1, 0;"
               : "+r"(d[0]), "+r"(d[1]), "+r"(d[2]), "+r"(d[3]), "+r"(d[4]), "+r"(d[5]), "+r"(d[6]), "+r"(d[7]), "+r"(d[8]), "+r"(d[9]), "+r"(d[10]), "+r"(d[11])
               : "r"(a[0]), "r"(a[1]), "r"(a[2]), "r"(a[3]), "l"(db));
}
__device__ __forceinline__ void gemm_w2(uint32_t* d, const uint32_t* a, uint64_t dw) {
  wg_fence();
#pragma unroll
  for (int k = 0; k < 6; k++) {
    wg48h(d, a + 4 * k, dw + (k >> 1) * 384 + (k & 1) * 2); wg48h(d + 12, a + 4 * k, dw + (k >> 1) * 384 + (k & 1) * 2 + 192);
  }
  wg_commit();
}
template <int kChains = 2>
__device__ __forceinline__ uint32_t sumsq(const uint32_t* z) {
  if (kChains == 1) {
    uint32_t a = h2mul(z[0], z[0]), b = h2mul(z[1], z[1]);
#pragma unroll
    for (int j = 1; j < 12; j++) { a = h2fma(z[2 * j], z[2 * j], a); b = h2fma(z[2 * j + 1], z[2 * j + 1], b); }
    return fold_add(a, b);
  }
  uint32_t q0[2], q1[2];
#pragma unroll
  for (int j = 0; j < 12; j++) {
    const uint32_t u = z[2 * j], v = z[2 * j + 1];
    q0[j & 1] = j < 2 ? h2mul(u, u) : h2fma(u, u, q0[j & 1]); q1[j & 1] = j < 2 ? h2mul(v, v) : h2fma(v, v, q1[j & 1]);
  }
  return fold_add(h2add(q0[0], q0[1]), h2add(q1[0], q1[1]));
}
__device__ __forceinline__ uint32_t rowsum(const uint32_t* z) {
  uint32_t a[2], b[2];
#pragma unroll
  for (int r = 0; r < 2; r++) {
    a[r] = h2add(h2add(h2add(z[r], z[r + 2]), h2add(z[r + 4], z[r + 6])), h2add(z[r + 8], z[r + 10]));
    b[r] = h2add(h2add(h2add(z[r + 12], z[r + 14]), h2add(z[r + 16], z[r + 18])), h2add(z[r + 20], z[r + 22]));
  }
  return fold_add(h2add(a[0], b[0]), h2add(a[1], b[1]));
}
__device__ __forceinline__ void scores_e(uint32_t* e, const uint32_t* q, const uint32_t* z) {
  uint32_t d[4];
#pragma unroll
  for (int j = 0; j < 12; j++) {
#pragma unroll
    for (int k = 0; k < 4; k++) d[k] = j ? h2fma(q[2 * j + (k >> 1)], z[2 * j + (k & 1)], d[k]) : h2mul(q[k >> 1], z[k & 1]);
  }
  e[0] = fold_add(d[0], d[2]); e[1] = fold_add(d[1], d[3]);
}
__device__ __forceinline__ uint32_t scores_r(const uint32_t* e, uint32_t selK) {
  return h2add(prmt(e[0], e[1], selK), __shfl_xor_sync(0xffffffffu, prmt(e[0], e[1], selK ^ 0x2222u), 1));
}
__device__ __forceinline__ uint32_t scores(const uint32_t* q, const uint32_t* z, uint32_t selK) {
  uint32_t e[2];
  scores_e(e, q, z);
  return scores_r(e, selK);
}
__device__ __forceinline__ float2 rstd(float2 d) { return make_float2(rsq_fast(fmaf(d.x, 1.f / 96.f, 1e-5f)), rsq_fast(fmaf(d.y, 1.f / 96.f, 1e-5f))); }
__device__ __forceinline__ void ln1_f32(uint32_t* z, const A3& la, int t, float* ie, float* m) {
  float acc[48];
  uint32_t x0[12], x1[12];
  load_row(x0, la, t); load_row(x1, la, t + 1);
#pragma unroll
  for (int j = 0; j < 12; j++) {
    acc[4 * j] = __uint_as_float(x0[j] << 16); acc[4 * j + 1] = __uint_as_float(x0[j] & 0xffff0000u);
    acc[4 * j + 2] = __uint_as_float(x1[j] << 16); acc[4 * j + 3] = __uint_as_float(x1[j] & 0xffff0000u);
  }
  float s[4], q[4];
#pragma unroll
  for (int e = 0; e < 4; e++) { s[e] = acc[e]; q[e] = acc[e] * acc[e]; }
#pragma unroll
  for (int j = 4; j < 48; j++) { s[j & 3] += acc[j]; q[j & 3] = fmaf(acc[j], acc[j], q[j & 3]); }
  const float s0 = quad_sum(s[0] + s[1]), s1 = quad_sum(s[2] + s[3]), q0 = quad_sum(q[0] + q[1]), q1 = quad_sum(q[2] + q[3]);
  const float u0 = rsq_fast(fmaxf(fmaf(-s0, s0, fmaf(q0, 96.f, kEps96)), kEps96));
  const float u1 = rsq_fast(fmaxf(fmaf(-s1, s1, fmaf(q1, 96.f, kEps96)), kEps96));
  const float n0 = -s0 * u0, n1 = -s1 * u1;
  ie[0] = 96.f * u0; ie[1] = 96.f * u1;
  m[0] = s0 * (1.f / 96.f); m[1] = s1 * (1.f / 96.f);
#pragma unroll
  for (int j = 0; j < 12; j++) {
    const int e = 4 * (j & ~1) + (j & 1);
    z[2 * j] = pack_h2(fmaf(acc[e], ie[0], n0), fmaf(acc[e + 4], ie[0], n0));
    z[2 * j + 1] = pack_h2(fmaf(acc[e + 2], ie[1], n1), fmaf(acc[e + 6], ie[1], n1));
  }
}
__device__ __forceinline__ float2 sumsq_f32(const uint32_t* z) {
  float2 qq = make_float2(0.f, 0.f);
#pragma unroll
  for (int j = 0; j < 12; j++) {
    const float2 u = unpack_h2(z[2 * j]), v = unpack_h2(z[2 * j + 1]);
    qq.x = fmaf(u.x, u.x, fmaf(u.y, u.y, qq.x)); qq.y = fmaf(v.x, v.x, fmaf(v.y, v.y, qq.y));
  }
  return make_float2(quad_sum(qq.x), quad_sum(qq.y));
}
__device__ __forceinline__ float2 var96_f32(const uint32_t* z, uint32_t my) {
  const float2 q = sumsq_f32(z), m = unpack_h2(my);
  return make_float2(fmaf(-96.f * m.x, m.x, q.x), fmaf(-96.f * m.y, m.y, q.y));
}
__device__ __forceinline__ void ln2(uint32_t* h, uint32_t rr, uint32_t my, const A3& ma, int t) {
  const uint32_t nn = as_u(__hmul2(__hneg2(as_h2(my)), as_h2(rr)));
#pragma unroll
  for (int j = 0; j < 12; j++) { h[2 * j] = h2fma(h[2 * j], lo2(rr), lo2(nn)); h[2 * j + 1] = h2fma(h[2 * j + 1], hi2(rr), hi2(nn)); }
#pragma unroll
  for (int k = 0; k < 3; k++) { stsm4(ma.a[k] + t * kFrame, h + 8 * k); stsm4((ma.a[k] ^ 32) + t * kFrame, h + 8 * k + 4); }
}

__device__ __forceinline__ uint32_t ring_pos(uint32_t r) { return min(r, r - 196u); }
__device__ __forceinline__ uint32_t ring_row(uint32_t r) { return ((r * 1338u) >> 16) * (kBufStride - kChunk) + r * 64; }
__device__ __forceinline__ uint32_t ring_stat(uint32_t r) { return ((r * 1338u) >> 16) * (kBufStride - 49 * 4) + r * 4; }
__device__ __forceinline__ A3 t_in_addr(uint32_t sb, uint32_t r0, int lane) {
  return swz3(sb + kOffBuf + (lane & 3) * 16 + ring_row(ring_pos(r0 + (lane >> 2))));
}
__device__ __forceinline__ A3 t_out_addr(uint32_t sb, uint32_t r0, int lane) {
  return swz3(sb + kOffBuf + ((lane >> 3) & 1) * kFrame + (lane & 16) + ring_row(ring_pos(r0 + (lane & 7))));
}
__device__ __forceinline__ uint32_t t_stat_addr(uint32_t sb, uint32_t r0, int lane) {
  return sb + kOffBuf + kXBytes + (lane & 3) * kFrame + ring_stat(ring_pos(r0 + (lane >> 2)));
}
__device__ __forceinline__ void t_release(uint32_t bar, uint32_t ia, uint32_t ib, int lane) {
  __syncwarp();
  asm volatile("{\n.reg .pred p;\nsetp.le.u32 p, %1, %2;\n@p mbarrier.arrive.shared::cta.b64 _, [%0];\n}"
               ::"r"(bar + ((ia + lane) & 3) * 8), "r"(lane), "r"(ib - ia) : "memory");
}
template <bool kDirect>
__device__ __forceinline__ void softmax4(uint32_t* s, uint32_t rhoA, uint32_t rhoB, uint32_t ro, float f) {
  if (kDirect) { s[0] = h2mul(s[0], rhoA); s[1] = h2mul(s[1], rhoB); }
  uint32_t mx = h2max(s[0], s[1]);
  mx = h2max(lo2(mx), hi2(mx));
  if (kDirect) {
    const uint32_t nm = as_u(__hmul2(__hneg2(as_h2(mx)), as_h2(ro)));
    s[0] = h2fma(s[0], ro, nm); s[1] = h2fma(s[1], ro, nm);
  } else {
    s[0] = h2mul(h2sub(s[0], mx), ro); s[1] = h2mul(h2sub(s[1], mx), ro);
  }
  s[0] = h2ex2(s[0]); s[1] = h2ex2(s[1]);
  uint32_t sm = h2add(s[0], s[1]);
  sm = h2add(lo2(sm), hi2(sm));
  const float iv = f * rcp_fast(__low2float(as_h2(sm)));
  const uint32_t inv = pack_h2(iv, iv);
  if (kDirect) { s[0] = h2mul(h2mul(s[0], rhoA), inv); s[1] = h2mul(h2mul(s[1], rhoB), inv); }
  else { s[0] = h2mul(s[0], inv); s[1] = h2mul(s[1], inv); }
}
template <bool kFirst>
__device__ __forceinline__ void mix(uint32_t* u, const uint32_t* z, uint32_t p0, uint32_t p1) {
#pragma unroll
  for (int j = 0; j < 12; j++) {
    u[2 * j] = h2fma(z[2 * j + 1], hi2(p0), kFirst ? h2mul(z[2 * j], lo2(p0)) : h2fma(z[2 * j], lo2(p0), u[2 * j]));
    u[2 * j + 1] = h2fma(z[2 * j + 1], hi2(p1), kFirst ? h2mul(z[2 * j], lo2(p1)) : h2fma(z[2 * j], lo2(p1), u[2 * j + 1]));
  }
}
template <bool kDirect>
__device__ __forceinline__ void put_stats(uint32_t sa, float sg, float mm, const Params& P) {
  const bool ok = (sg >= P.sgmin) & (kDirect || fmaf(sg, 9.8f, fabsf(mm)) < fmaf(P.kappa, -627.2f, 60000.f));
  const uint32_t sh = pack_h2(sg, mm), sw = pack_bf2(-sg, mm);
  asm volatile("st.shared.b32 [%0], %1;" ::"r"(sa), "r"(ok ? sh : sw) : "memory");
}

__device__ __forceinline__ bool task_T(uint32_t sb, uint32_t r0, uint32_t ia, uint32_t ib, uint32_t flag, int lane, const Params& P TRARG) {
  TR(1);
  const int c = lane & 3;
  const uint32_t selK = (c & 1) ? 0x7632u : 0x5410u, selO = 0x1010u + c * 0x2222u;
  const uint64_t da = mk_desc(sb, 1), dw = mk_desc(sb + kOffWt, 1);
  uint32_t x[48], yA[24], yB[24], qA[26], qB[26], ssA, ssB;
  {
    const A3 la = t_in_addr(sb, r0, lane);
#pragma unroll
    for (int e = 0; e < 12; e++) {
      const int t = 2 * (e / 6) + (e & 1), k = (e % 6) >> 1, ep = e - SM, tp = 2 * (ep / 6) + (ep & 1), kp = (ep % 6) >> 1;
      if (ep >= 0) hold(sb, x[12 * tp + 4 * kp]);
      lds128(x + 12 * t + 4 * k, la.a[k] + t * kFrame);
    }
  }
  row_to_h2(yA, x); row_to_h2(yA + 1, x + 12);
  x_work<7>(sb, x[5]);
  TR(2);
  row_to_h2(yB, x + 24); row_to_h2(yB + 1, x + 36);
  ssB = sumsq<C1>(yB);
  ssA = sumsq<C1>(yA);
  if (SPL & 1) gemm_at2(qA, yA, da); else gemm_at(qA, yA, da);
  if (SPL & 2) gemm_at2(qB, yB, da); else gemm_at(qB, yB, da);
  TR(3);
  ssB = quad_h2add(ssB);
  ssA = quad_h2add(ssA);
  uint32_t rA[2], rB[2];
  wg_wait<1>(); pin<26>(qA);
  x_work<11>(sb, qA[5]);
  TR(4);
  const uint32_t myA = __byte_perm(qA[24], qA[25], 0x5410), nuA = __byte_perm(qA[24], qA[25], 0x7632);
  const uint32_t nsA = h2mul(myA, 0xd600d600u);
  const float2 ra = rstd(unpack_h2(h2fma(nsA, myA, ssA)));
  const uint32_t rhoA = pack_h2(ra.x, ra.y);
  rA[0] = scores(qA, yA, selK);
  if (HD & 2) { hold(sb, rA[0]); hold(sb, rhoA); } else sched_fence(rA[0], rhoA, 0);
  wg_wait<0>(); pin<26>(qB);
  TR(5);
  const uint32_t myB = __byte_perm(qB[24], qB[25], 0x5410), nuB = __byte_perm(qB[24], qB[25], 0x7632);
  const uint32_t nsB = h2mul(myB, 0xd600d600u);
  const float2 rb = rstd(unpack_h2(h2fma(nsB, myB, ssB)));
  const uint32_t rhoB = pack_h2(rb.x, rb.y);
  const uint32_t ro = prmt(rhoA, rhoB, selO), mo = bitsel(prmt(myA, myB, selO), 0xffffu, 0x292e0000u);
  asm volatile("{\n.reg .pred p, q;\n.reg .b32 t;\nabs.f16x2 t, %1;\nsetp.gtu.f16x2 p|q, t, %2;\nor.pred p, p, q;\n@p st.volatile.shared.b32 [%0], %2;\n}"
               ::"r"(flag), "r"(h2fma(ro, mo, 0xbc190000u)), "r"(0x3c003c00u) : "memory");
  uint32_t mu;
  rA[1] = scores(qA, yB, selK); rB[0] = scores(qB, yA, selK); rB[1] = scores(qB, yB, selK);
  uint32_t p[8], s[2];
#pragma unroll
  for (int k = 0; k < 2; k++) s[k] = h2add((c & 2) ? rB[k] : rA[k], __shfl_xor_sync(0xffffffffu, (c & 2) ? rA[k] : rB[k], 2));
  softmax4<true>(s, rhoA, rhoB, ro, P.kt);
#pragma unroll
  for (int t = 0; t < 4; t++) { p[2 * t] = __shfl_sync(0xffffffffu, s[0], t, 4); p[2 * t + 1] = __shfl_sync(0xffffffffu, s[1], t, 4); }
  mu = h2fma(s[1], nuB, h2mul(s[0], nuA));
  mix<true>(qA, yA, p[0], p[2]); mix<false>(qA, yB, p[1], p[3]);
  mu = h2add(lo2(mu), hi2(mu));
  mix<true>(qB, yA, p[4], p[6]);
  x_work<8>(sb, p[4]);
  TR(6);
  if (SPL & 4) gemm_w2(yA, qA, dw); else gemm_w<1>(yA, qA, dw);
  sched_fence(0, 0, 0);
  mix<false>(qB, yB, p[5], p[7]);
  if (SPL & 8) gemm_w2(yB, qB, dw); else gemm_w<1>(yB, qB, dw);
  const A3 ma = t_out_addr(sb, r0, lane);
  if (HD & 4) hold(sb, ma.a[0] ^ ma.a[1] ^ ma.a[2]);
  x_work<9>(sb, mu);
  TR(7);
  wg_wait<1>(); pin<24>(yA);
  TR(8);
  uint32_t bad;
  asm volatile("ld.shared.b32 %0, [%1];" : "=r"(bad) : "r"(flag + (yA[0] & (gridDim.x == 0x7fffffffu))) : "memory");
  float2 d = unpack_h2(h2fma(nsA, myA, quad_h2add(sumsq<C2>(yA))));
  if (UNLIKELY(__any_sync(0xffffffffu, !(d.x + d.y < 65000.f) | (bad != 0)))) {
    if (__any_sync(0xffffffffu, bad != 0)) {
      wg_wait<0>(); pin<24>(yB);
      return false;
    }
    d = var96_f32(yA, myA);
  }
  float2 r = rstd(make_float2(fabsf(d.x), fabsf(d.y)));
  const uint32_t rrA = pack_h2(r.x, r.y);
  ln2(yA, rrA, myA, ma, 0);
  if (DA) t_release(sb + kOffBar + 32, ia, ib, lane);
  wg_wait<0>(); pin<24>(yB);
  x_work<10>(sb, yB[5]);
  TR(9);
  d = unpack_h2(h2fma(nsB, myB, quad_h2add(sumsq<C2>(yB))));
  if (UNLIKELY(__any_sync(0xffffffffu, !(d.x + d.y < 65000.f)))) d = var96_f32(yB, myB);
  r = rstd(make_float2(fabsf(d.x), fabsf(d.y)));
  const uint32_t rrB = pack_h2(r.x, r.y);
  ln2(yB, rrB, myB, ma, 2);
  put_stats<true>(t_stat_addr(sb, r0, lane), rcp_fast(__low2float(as_h2(prmt(rrA, rrB, selO)))), __low2float(as_h2(CM ? prmt(myA, myB, selO) : h2add(mo, mu))), P);
  return true;
}

__device__ __forceinline__ void task_T_general(uint32_t sb, uint32_t r0, const Params& P) {
  int lane;
  asm volatile("mov.u32 %0, %%laneid;" : "=r"(lane));
  const int c = lane & 3;
  const uint64_t da = mk_desc(sb, 1), dw = mk_desc(sb + kOffWt, 1);
  uint32_t yA[24], yB[24], qA[26], qB[26];
  float ieo, mo, ao;
  {
    float ie[4], m[4];
    const A3 la = t_in_addr(sb, r0, lane);
    ln1_f32(yA, la, 0, ie, m);
    ln1_f32(yB, la, 2, ie + 2, m + 2);
    const float2 na = sumsq_f32(yA), nb = sumsq_f32(yB);
    const float ik = 9.8f * rcp_fast(P.kt) * rsq_fast(fmaxf(fmaxf(fmaxf(na.x, na.y), fmaxf(nb.x, nb.y)), 2e-7f));
    ieo = (c & 2) ? ((c & 1) ? ie[3] : ie[2]) : ((c & 1) ? ie[1] : ie[0]);
    mo = (c & 2) ? ((c & 1) ? m[3] : m[2]) : ((c & 1) ? m[1] : m[0]);
    const bool lim = (ieo * P.kt > 400.f) & (ik < ieo);
    const float u = ik * rcp_fast(ieo);
    ao = lim ? u : 1.f; ieo = lim ? ik : ieo;
  }
  uint32_t rA[2], rB[2], s[2], p[8];
  const uint32_t selK = (c & 1) ? 0x7632u : 0x5410u;
  gemm_at(qA, yA, da);
  wg_wait<0>(); pin<26>(qA);
  const uint32_t nuA = __byte_perm(qA[24], qA[25], 0x7632);
  rA[0] = scores(qA, yA, selK); rA[1] = scores(qA, yB, selK);
  sched_fence(rA[0], rA[1], nuA);
  gemm_at(qB, yB, da);
  wg_wait<0>(); pin<26>(qB);
  const uint32_t nuB = __byte_perm(qB[24], qB[25], 0x7632);
  rB[0] = scores(qB, yA, selK); rB[1] = scores(qB, yB, selK);
#pragma unroll
  for (int k = 0; k < 2; k++) s[k] = h2add((c & 2) ? rB[k] : rA[k], __shfl_xor_sync(0xffffffffu, (c & 2) ? rA[k] : rB[k], 2));
  softmax4<false>(s, 0, 0, score_scale(&g_par.cS_t), P.kt * ieo);
  uint32_t mu = h2fma(s[1], nuB, h2mul(s[0], nuA));
  mu = h2add(lo2(mu), hi2(mu));
#pragma unroll
  for (int t = 0; t < 4; t++) { p[2 * t] = __shfl_sync(0xffffffffu, s[0], t, 4); p[2 * t + 1] = __shfl_sync(0xffffffffu, s[1], t, 4); }
  sched_fence(mu, 0, 0);
  mix<true>(qA, yA, p[0], p[2]); mix<false>(qA, yB, p[1], p[3]);
  mix<true>(qB, yA, p[4], p[6]); mix<false>(qB, yB, p[5], p[7]);
  const uint32_t ah = pack_h2(ao, ao);
#pragma unroll
  for (int t = 0; t < 4; t++) {
    const uint32_t a = __shfl_sync(0xffffffffu, ah, t, 4);
#pragma unroll
    for (int j = 0; j < 12; j++) asm volatile("mul.f16x2 %0, %0, %1;" : "+r"(((t & 2) ? yB : yA)[2 * j + (t & 1)]) : "r"(a));
  }
  gemm_w<1>(yA, qA, dw);
  gemm_w<1>(yB, qB, dw);
  wg_wait<0>(); pin<24>(yA); pin<24>(yB);
  asm volatile("mov.u32 %0, %%laneid;" : "=r"(lane));
  float ie[4];
#pragma unroll
  for (int t = 0; t < 4; t++) ie[t] = __shfl_sync(0xffffffffu, ieo, t, 4);
  const float2 da2 = sumsq_f32(yA), db2 = sumsq_f32(yB);
  const uint32_t rrA = pack_h2_sat(rsq_fast(fmaf(da2.x, 1.f / 96.f, 1e-5f * ie[0] * ie[0])), rsq_fast(fmaf(da2.y, 1.f / 96.f, 1e-5f * ie[1] * ie[1])));
  const uint32_t rrB = pack_h2_sat(rsq_fast(fmaf(db2.x, 1.f / 96.f, 1e-5f * ie[2] * ie[2])), rsq_fast(fmaf(db2.y, 1.f / 96.f, 1e-5f * ie[3] * ie[3])));
  const A3 ma = t_out_addr(sb, r0, lane);
  ln2(yA, rrA, 0u, ma, 0); ln2(yB, rrB, 0u, ma, 2);
  const float r = __low2float(as_h2(prmt(rrA, rrB, 0x1010u + (lane & 3) * 0x2222u))), sg = rcp_fast(r * ieo);
  put_stats<false>(t_stat_addr(sb, r0, lane), sg, fmaf(__low2float(as_h2(mu)) * r, sg, mo), P);
}

__device__ __forceinline__ void claim(uint32_t sb, uint32_t nfull) {
  const uint32_t nb = gridDim.x, nrem = kNWIN - nfull * nb;
  const uint32_t whole = max((int)(nrem * NWH / 49), (int)(2 * nrem - nb));
  uint32_t t = blockIdx.x;
  if (DYN) asm volatile("atom.relaxed.gpu.global.inc.u32 %0, [%1], 0x7fffffff;" : "=r"(t) : "l"(&g_ctr) : "memory");
  const uint32_t u = t - whole;
  sts32(sb + kOffClaim, t < whole ? (nfull * nb + t) | 0x10000u
                        : u < 2 * (nrem - whole) ? (nfull * nb + whole + (u >> 1)) | 0x50000u | ((u & 1) << 17)
                        : blockIdx.x + (nfull - 1) * nb);
}
__device__ __forceinline__ void loop_T(uint32_t sb, int nfull, int wg, int wp, int lane, const Params& P, bool direct TRARG) {
  const uint32_t barF = sb + kOffBar, barD = sb + (DA ? kOffBarB : kOffBar + 32), flag = sb + kOffFlag + wg * 4;
  mbar_wait(sb + kOffBarW, 0);
  uint32_t r0 = 32 * wg + 8 * wp, par = 0;
  int k = (49 * nfull + 63 - 32 * wg) >> 6;
  int kx = ((49 * nfull + 112 - 32 * wg) >> 6) - k;
  int kc = wg + wp ? 0 : k - ((49 * (nfull - 3) - 1) >> 6);
  for (;;) {
    TR(0);
    if (UNLIKELY(k <= kc)) {
      if (k) {
        if (lane == 0) claim(sb, nfull);
        __syncwarp();
        kc = 0;
      } else {
        mbar_wait(barF + (nfull & 3) * 8, (nfull >> 2) & 1);
        k = __any_sync(0xffffffffu, lds32(sb + kOffClaim) & 0x10000u) ? kx : 0;
        kx = 0;
        if (k == 0) break;
      }
    }
    k--;
    const uint32_t ia = (r0 * 1338u) >> 16, ib = ((r0 + 7) * 1338u) >> 16;
    mbar_wait(barF + ia * 8, par);
    if (UNLIKELY(ib != ia)) mbar_wait(barF + (ib & 3) * 8, par ^ (ib >> 2));
    const uint32_t r = r0;
    r0 += 64;
    if (r0 >= 196) { r0 -= 196; par ^= 1; }
    if (LIKELY(direct)) {
      if (LIKELY(task_T(sb, r, ia, ib, flag, lane, P TRPASS(trp)))) {
        t_release(barD, ia, ib, lane);
        continue;
      }
      asm volatile("barrier.cta.sync.aligned %0, 128;" ::"r"(wg + 1) : "memory");
      asm volatile("st.shared.b32 [%0], %1;\nfence.acq_rel.cta;" ::"r"(flag), "r"(0) : "memory");
    }
    task_T_general(sb, r, P);
    if (DA) t_release(sb + kOffBar + 32, ia, ib, lane);
    t_release(barD, ia, ib, lane);
  }
}

struct SFrame {
  uint32_t oo;
  uint32_t t;
  uint32_t st;
  uint32_t d;
  bool light;
};
__device__ __forceinline__ SFrame s_frame(uint32_t sb, int t, int wp, int lane, A3& ma) {
  SFrame f;
  const int rb = (wp + t) & 3;
  f.light = rb == 3;
  f.t = t;
  f.d = ((sb + kOffBuf + t * kFrame) >> 4) & 0x3fff;
  f.st = t * kFrame + kXBytes + rb * 64;
  ma = swz3(t * kFrame + rb * 1024 + ((lane * 65) & 0x3d0));
  if (f.light && (lane & 15)) ma.a[0] = ma.a[1] = ma.a[2] = kXBytes + 256;
  const uint32_t r = 16 * rb + (lane >> 2);
  f.oo = (r + (r / 7) * (kW - 7)) * 12 + (lane & 3) + (((r + 8 + ((r + 8) / 7) * (kW - 7)) * 12 + (lane & 3)) << 16);
  asm volatile("" : "+r"(f.oo));
  return f;
}
template <int kRow>
__device__ __forceinline__ uint8_t* out_row(uint8_t* ob, const SFrame& f) {
  uint32_t o = f.oo;
  asm volatile("" : "+r"(o));
  uint8_t* r;
  asm("mad.wide.u32 %0, %1, 16, %2;" : "=l"(r) : "r"(kRow ? o >> 16 : o & 0xffffu), "l"(ob));
  return r;
}
template <int kHi, int kFrom = 0, int kTo = 6>
__device__ __forceinline__ void s_load(uint32_t (&v)[24], uint32_t buf, A3 ma) {
  asm volatile("" : "+r"(ma.a[0]), "+r"(ma.a[1]), "+r"(ma.a[2]));
#pragma unroll
  for (int e = kFrom; e < kTo; e++) {
    const uint32_t a = kHi ? ma.a[e >> 1] >> 16 : ma.a[e >> 1] & 0xffffu;
    ldsm4(v + 4 * e, buf + ((e & 1) ? a ^ 32 : a));
  }
}
__device__ __forceinline__ void gemm_s(uint32_t* s, const uint32_t* q, uint64_t dA) {
  wg_fence();
  wg56h<0>(s, q, dA); wg56h<1>(s, q + 4, dA + 2);
  wg56h<1>(s, q + 8, dA + 196); wg56h<1>(s, q + 12, dA + 198);
  wg56h<1>(s, q + 16, dA + 392); wg56h<1>(s, q + 20, dA + 394);
  wg_commit();
}
template <bool kAll>
__device__ __forceinline__ void stg128(uint8_t* o, const uint32_t* w, uint32_t doit) {
  if (kAll) asm volatile("st.global.v4.b32 [%0], {%1,%2,%3,%4};" ::"l"(o), "r"(w[0]), "r"(w[1]), "r"(w[2]), "r"(w[3]) : "memory");
  else asm volatile("{\n.reg .pred p;\nsetp.ne.u32 p, %5, 0x7bff;\n@p st.global.v4.b32 [%0], {%1,%2,%3,%4};\n}" ::"l"(o), "r"(w[0]), "r"(w[1]), "r"(w[2]), "r"(w[3]), "r"(doit) : "memory");
}
template <int kRow, bool kAll>
__device__ __forceinline__ void s_store(const uint32_t (&v)[24], uint32_t e, uint8_t* o) {
  uint32_t w[12];
#pragma unroll
  for (int j = 0; j < 12; j += 2) {
    const float2 y = unpack_h2(h2fma(v[2 * j + kRow], lo2(e), hi2(e))), z = unpack_h2(h2fma(v[2 * j + 2 + kRow], lo2(e), hi2(e)));
    w[j] = pack_bf2(y.x, z.x); w[j + 1] = pack_bf2(y.y, z.y);
  }
#pragma unroll
  for (int i3 = 0; i3 < 3; i3++) stg128<kAll>(o + 64 * i3, w + 4 * i3, e);
}
template <int kRow, bool kAdd>
__device__ __forceinline__ void s_store_wide(const uint32_t (&v)[24], uint32_t e, uint8_t* o, const Params& P) {
  const float2 z = stat_f32(e);
#pragma unroll
  for (int i3 = 0; i3 < 3; i3++) {
    uint32_t w[4] = {0, 0, 0, 0};
    if (kAdd)
      asm volatile("{\n.reg .pred p;\nsetp.ne.u32 p, %5, 0x7bff;\n@p ld.global.v4.b32 {%0,%1,%2,%3}, [%4];\n}"
                   : "+r"(w[0]), "+r"(w[1]), "+r"(w[2]), "+r"(w[3]) : "l"(o + 64 * i3), "r"(e) : "memory");
#pragma unroll
    for (int j = 0; j < 4; j++) {
      const float2 ya = unpack_h2(v[8 * i3 + 2 * (j & 2) + kRow]), yb = unpack_h2(v[8 * i3 + 2 * (j & 2) + 2 + kRow]);
      const float2 y = (j & 1) ? make_float2(ya.y, yb.y) : make_float2(ya.x, yb.x);
      w[j] = kAdd ? pack_bf2(fmaf(y.x, P.kappa, __uint_as_float(w[j] << 16)), fmaf(y.y, P.kappa, __uint_as_float(w[j] & 0xffff0000u)))
                  : pack_bf2(fmaf(y.x, z.x, z.y), fmaf(y.y, z.x, z.y));
    }
    stg128<false>(o + 64 * i3, w, e);
  }
  __syncwarp();
}
__device__ __forceinline__ uint32_t ex2_pair(uint32_t s, uint32_t sel) {
  uint32_t lo, hi;
  asm volatile("{\n.reg .b16 a, b, c;\nmov.b32 {a, b}, %2;\nex2.approx.f16 c, a;\ncvt.u32.u16 %0, c;\nex2.approx.f16 c, b;\ncvt.u32.u16 %1, c;\n}"
               : "=r"(lo), "=r"(hi) : "r"(s));
  return QP ? prmt(lo, hi, sel) : lo + hi * 65536u;
}
__device__ __forceinline__ uint32_t ex2_lo(uint32_t s) {
  uint32_t lo;
  asm volatile("{\n.reg .b16 a, b, c;\nmov.b32 {a, b}, %1;\nex2.approx.f16 c, a;\ncvt.u32.u16 %0, c;\n}" : "=r"(lo) : "r"(s));
  return lo;
}

__device__ __forceinline__ void turn_wait(uint32_t j) { asm volatile("barrier.cta.sync.aligned %0, 256;" ::"r"(5 + j) : "memory"); }
__device__ __forceinline__ void turn_pass(uint32_t j) { asm volatile("barrier.cta.arrive.aligned %0, 256;" ::"r"(6 - j) : "memory"); }

template <int kSecond>
__device__ __forceinline__ void step_S(uint32_t sb, uint32_t (&v)[24], uint32_t (&vn)[24], uint32_t (&q)[24], uint32_t (&s)[16], const SFrame& f,
                                       const SFrame& fn, const A3& ma, uint32_t i, uint32_t nfull, uint32_t w4, uint32_t& cl, uint8_t* ob, int lane, const Params& P,
                                       bool scaled, const CUtensorMap* tm TRARG) {
  TR(0);
  const uint32_t ia = i & 3, ib = kSecond ? (i + 1) & 3 : ia;
  const uint32_t buf = sb + kOffBuf + ia * kBufStride, bufn = sb + kOffBuf + ib * kBufStride;
  const uint32_t never = gridDim.x == 0x7fffffffu;
  const uint64_t dQ0 = mk_desc(sb + kOffAs, 1), dQ = (HQ & 1) ? dQ0 : dQ0 + ((i + kSecond) & never), dW = ((HQ & 2) ? dQ0 : dQ0 + ((i + kSecond) & never)) + (kWMat >> 4);
  uint32_t p[16], u[24], e0, e1;
  ob += f.t * (kH * kW * 192u);
  const uint32_t nw = nfull + ((cl >> 16) & 1);
  asm volatile("" : "+l"(ob));
  uint32_t g4 = lane;
  asm volatile("" : "+r"(g4));
  uint32_t stu = buf + f.st;
  asm volatile("" : "+r"(stu));
  const uint32_t sta = stu + (g4 & 0x1c);
  asm volatile("ld.shared.b32 %0, [%1];" : "=r"(e0) : "r"(sta) : "memory");
  asm volatile("ld.shared.b32 %0, [%1];" : "=r"(e1) : "r"(sta + 32) : "memory");
  constexpr int kLP = kSecond ? LP1 : LP0;
  auto loadp = [&](int pos) {
    if (pos != kLP) return;
    if (kSecond && i + 1 < nw) mbar_wait(sb + kOffBar + 32 + ib * 8, ((i + 1) >> 2) & 1);
    s_load<!kSecond, 0, LA>(vn, bufn, ma);
  };
  loadp(2);
  const uint32_t keep = (lane & 3) == 0 ? 0x0000ffffu : 0u;
  const bool pad0 = QP && f.light && lane >= 4, pad1 = QP && f.light;
  const uint32_t sel0 = pad0 ? 0x3232u : 0x5410u, sel1 = pad1 ? 0x3232u : 0x5410u;
  s[12] = bitsel(s[12], QP == 1 && pad0 ? 0u : keep, 0xfc00fc00u); s[13] = bitsel(s[13], QP == 1 && pad1 ? 0u : keep, 0xfc00fc00u);
  const uint32_t x0 = h2max(h2max(h2max(h2max(s[0], s[2]), s[4]), h2max(h2max(s[6], s[8]), s[10])), s[12]);
  const uint32_t x1 = h2max(h2max(h2max(h2max(s[1], s[3]), s[5]), h2max(h2max(s[7], s[9]), s[11])), s[13]);
  const bool ok = __hble2(__hmax2(__habs2(as_h2(x0)), __habs2(as_h2(x1))), as_h2(0x47004700u)) & !scaled;
  constexpr int kE = IL == 0 ? 12 : IL == 1 ? 4 : IL == 2 ? 0 : 8;
  p[12] = ex2_lo(s[12]); p[13] = ex2_lo(s[13]);
  if (QP == 3) { p[12] = prmt(p[12], 0, sel0); p[13] = prmt(p[13], 0, sel1); }
#pragma unroll
  for (int j = 0; j < kE; j++) p[j] = ex2_pair(s[j], (j & 1) ? sel1 : sel0);
  if (UNLIKELY(!__all_sync(0xffffffffu, ok))) {
    uint32_t mx = h2max(__byte_perm(x0, x1, 0x5410), __byte_perm(x0, x1, 0x7632));
    mx = h2max(mx, __shfl_xor_sync(0xffffffffu, mx, 1));
    mx = h2max(mx, __shfl_xor_sync(0xffffffffu, mx, 2));
    const uint32_t cs = lds32(sb + kOffCs);
#pragma unroll
    for (int j = 0; j < 7; j++) { s[2 * j] = h2mul(h2sub(s[2 * j], lo2(mx)), cs); s[2 * j + 1] = h2mul(h2sub(s[2 * j + 1], hi2(mx)), cs); }
    p[12] = ex2_lo(s[12]); p[13] = ex2_lo(s[13]);
  if (QP == 3) { p[12] = prmt(p[12], 0, sel0); p[13] = prmt(p[13], 0, sel1); }
#pragma unroll
    for (int j = 0; j < kE; j++) p[j] = ex2_pair(s[j], (j & 1) ? sel1 : sel0);
  }
  asm volatile("mov.b32 %0, 0;\nmov.b32 %1, 0;" : "=r"(p[14]), "=r"(p[15]));
  x_work<1>(sb, s[5]);
  TR(1);
  const uint64_t mn = OB ? desc_at(f.d + ia * (kBufStride >> 4) + (kChunk >> 4 << 16)) : mk_desc(buf + f.t * kFrame, kChunk >> 4);
  wg_fence();
  wg96h<2, 1>(q, p + 12, mn + 192, never); wg96h<1, 1>(q, p, mn);
  loadp(1);
#pragma unroll
  for (int j = 4; j < 12; j++) p[j] = ex2_pair(s[j], (j & 1) ? sel1 : sel0);
  loadp(4);
  const bool wide = __any_sync(0xffffffffu, ((e0 | e1) & 0x8000u) != 0u);
  uint32_t rs = fold_add(h2add(h2add(h2add(p[0], p[2]), p[12]), h2add(h2add(p[4], p[6]), h2add(p[8], p[10]))),
                         h2add(h2add(h2add(p[1], p[3]), p[13]), h2add(h2add(p[5], p[7]), h2add(p[9], p[11])))), rt;
  asm volatile("shfl.sync.bfly.b32 %0, %1, 1, 31, 0xffffffff;" : "=r"(rt) : "r"(rs));
  uint32_t r2, r3;
  asm volatile("shfl.sync.bfly.b32 %0, %1, 2, 31, 0xffffffff;" : "=r"(r2) : "r"(rs));
  asm volatile("shfl.sync.bfly.b32 %0, %1, 3, 31, 0xffffffff;" : "=r"(r3) : "r"(rs));
  wg_fence();
  wg96h<1, 1>(q, p + 4, mn + 64); wg96h<1, 1>(q, p + 8, mn + 128);
  wg_commit();
  loadp(5);
  TR(2);
  float g0 = __low2float(as_h2(e0)), g1 = __low2float(as_h2(e1));
  if (UNLIKELY(wide)) {
    s_store_wide<0, false>(v, e0, out_row<0>(ob, f), P); s_store_wide<1, false>(v, e1, out_row<1>(ob, f), P);
    asm volatile("mov.b32 %0, %2;\nmov.b32 %1, %2;" : "=f"(g0), "=f"(g1) : "f"(P.kappa));
  }
  rs = h2add(rs, rt);
  rt = h2add(r2, r3);
  auto next = [&]() {
    if (i + 1 < nw) mbar_wait(sb + kOffBar + 32 + ib * 8, ((i + 1) >> 2) & 1);
    s_load<0>(vn, bufn, ma);
  };
  loadp(0);
  rs = h2add(rs, rt);
  const float d0 = __low2float(as_h2(rs)), d1 = __high2float(as_h2(rs));
  const float c0 = P.kappa * rcp_fast(d0 * g0), c1 = P.kappa * rcp_fast(d1 * g1);
  const uint32_t cb = OA == 3 ? pack_h2_sat(c0, c1) : OA == 2 ? pack_h2_rz(c0, c1) : OA ? pack_h2(c0, c1) : pack_h2(e0 != kPadStat ? c0 : 0.f, e1 != kPadStat ? c1 : 0.f);
  if (kLP == 7) hold(sb, cb);
  loadp(7);
  x_work<2>(sb, e0);
  if (HD & 1) hold(sb, cb);
  if (PG == 1) turn_wait(f.t & 1);
  wg_wait<0>(); pin<24>(q);
  s_load<!kSecond, LA, LB2>(vn, bufn, ma);
  x_work<3>(sb, q[5]);
  TR(3);
  if (PG == 2) turn_wait(f.t & 1);

  if (kSecond && LD == 2) next();
  auto refill = [&]() {
    if (EL) {
      if (f.light & (i + 4 <= nw)) {
        const uint32_t c = i + 4 >= nfull ? cl : w4;
        tma_load_elect<!kSecond>(buf + f.t * kFrame, tm, sb + kOffBar + ia * 8, c & 0xffffu, f.t ^ ((c >> 16) & 2), fn.t ^ ((c >> 16) & 2));
      }
    } else if (f.light) {
      const uint32_t bar = sb + kOffBar + ia * 8;
      if (lane == 0) {
        const uint32_t c = i + 4 >= nfull ? cl : w4;
        if (i + 4 <= nw) {
          tma_load(buf + f.t * kFrame, tm, bar, c & 0xffffu, f.t ^ ((c >> 16) & 2));
          if (!kSecond) tma_prefetch(tm, c & 0xffffu, fn.t ^ ((c >> 16) & 2));
        }
      }
      __syncwarp();
    }
  };
#pragma unroll
  for (int j = 0; j < 12; j++) { u[2 * j] = h2mul(q[2 * j], lo2(cb)); u[2 * j + 1] = h2mul(q[2 * j + 1], hi2(cb)); }
  if (PG == 3) turn_wait(f.t & 1);
  TR(4);
  gemm_w<2>(v, u, dW, !wide);
  if (PG && PR == 0) turn_pass(f.t & 1);
  if (LF && LB2 < 6) sched_fence(0, 0, 0);
  s_load<!kSecond, LB2, 6>(vn, bufn, ma);

  if (RF == 0 || ((RF == 1 || RF == 4) && kSecond)) refill();
  if (kSecond && LD == 0) next();
  gemm_w<2>(q, vn, dQ, never);
  if (RF == 2 || (RF == 1 && !kSecond)) refill();
  if (PG && PR == 1) turn_pass(f.t & 1);
  x_work<4>(sb, e0);
  TR(5);
  if (OH && kSecond && i + 1 < nw) mbar_wait(sb + kOffBarB + ib * 8, ((i + 1) >> 2) & 1);
  if (kSecond && UNLIKELY(i + 5 == nfull)) cl = __shfl_sync(0xffffffffu, lds32(sb + kOffClaim), 0);
  const bool plain = !(wide | f.light);
  wg_wait<1>(); pin<24>(v);
  if (kSecond || !OH) asm volatile("fence.proxy.async.shared::cta;" ::: "memory");
  if (PG && PR == 2) turn_pass(f.t & 1);
  x_work<5>(sb, v[5]);
  TR(6);
  if (LIKELY(plain)) s_store<0, true>(v, e0, out_row<0>(ob, f));
  else if (RF == 3 || (RF == 4 && !kSecond)) refill();
  if (PG && PR == 3) turn_pass(f.t & 1);
  wg_wait<0>(); pin<24>(q);
  TR(7);
  gemm_s(s, q, OB ? desc_at(fn.d + ib * (kBufStride >> 4) + (1 << 16)) : mk_desc(bufn + fn.t * kFrame, 1));
  if (PG && PR == 4) turn_pass(f.t & 1);

  if (LIKELY(plain)) s_store<1, true>(v, e1, out_row<1>(ob, f));
  else if (!wide) { s_store<0, false>(v, e0, out_row<0>(ob, f)); __syncwarp(); }
  else if (wide) { s_store_wide<0, true>(v, e0, out_row<0>(ob, f), P); s_store_wide<1, true>(v, e1, out_row<1>(ob, f), P); }
  if (kSecond && LP0 == 3) s_load<1>(v, bufn, ma);
  x_work<6>(sb, e0);
  if (PG && PR == 5) turn_pass(f.t & 1);
  if (!OH && kSecond && i + 1 < nw) mbar_wait(sb + kOffBarB + ib * 8, ((i + 1) >> 2) & 1);
  wg_wait<0>(); pin<14>(s);
}

__device__ __forceinline__ void loop_S(uint32_t sb, uint32_t nfull, int t0, int wp, int lane, const Params& P, bool scaled,
                                       const CUtensorMap* tm, uint8_t* __restrict__ out TRARG) {
  A3 ma, mb;
  const SFrame f0 = s_frame(sb, t0, wp, lane, ma), f1 = s_frame(sb, t0 + 2, wp, lane, mb);
#pragma unroll
  for (int k = 0; k < 3; k++) ma.a[k] += mb.a[k] << 16;
  uint32_t v0[24], v1[24], q[24], s[16];
  sts32(sb + kOffCs, pack_h2(P.cS_s, P.cS_s));
  mbar_wait(sb + kOffBarW + 8, 0);
  mbar_wait(sb + kOffBar + 32, 0);
  s_load<0>(v0, sb + kOffBuf, ma);
  gemm_w<0>(q, v0, mk_desc(sb + kOffAs, 1));
  if (OH) mbar_wait(sb + kOffBarB, 0);
  asm volatile("fence.proxy.async.shared::cta;" ::: "memory");
  wg_wait<0>(); pin<24>(q);
  gemm_s(s, q, mk_desc(sb + kOffBuf + f0.t * kFrame, 1));
  if (LP0 == 3) s_load<1>(v1, sb + kOffBuf, ma);
  wg_wait<0>(); pin<14>(s);
  if (PG && t0 == PF0) turn_pass(t0);
  uint32_t cl = 0, w0 = blockIdx.x;
  for (uint32_t i = 0;; i++, w0 += gridDim.x) {
    const bool more = i + 1 < nfull + ((cl >> 16) & 1);
    const uint32_t c = i == nfull ? cl : w0, w = c & 0xffffu;
    const uint32_t wy = (w * 57457u) >> 22;
    uint8_t* ob = out + (size_t)((wy * (7 * kW - 7 * kNWX) + w * 7 + ((c >> 16) & 2) * (kH * kW)) * 192u);
    asm volatile("" : "+l"(ob));
    step_S<0>(sb, v0, v1, q, s, f0, f1, ma, i, nfull, w0 + 4 * gridDim.x, cl, ob, lane, P, scaled, tm TRPASS(trp + 16 * i));
    if (c & 0x40000u) break;
    step_S<1>(sb, v1, v0, q, s, f1, f0, ma, i, nfull, w0 + 4 * gridDim.x, cl, ob, lane, P, scaled, tm TRPASS(trp + 16 * i + 8));
    if (!more) break;
  }
  if (PG && t0 != PF0) turn_wait(t0);
  const uint32_t nw = nfull + ((cl >> 16) & 1);
  mbar_wait(sb + kOffBar + (nw & 3) * 8, (nw >> 2) & 1);
}

__global__ void __launch_bounds__(LB, 1) swin_main(const __grid_constant__ Maps maps, uint8_t* __restrict__ out) {
  const CUtensorMap& tm = maps.tm;
  extern __shared__ __align__(1024) uint8_t smem[];
  const uint32_t sb = smem_u32(smem);
  const int tid = threadIdx.x;
  const int wg = __shfl_sync(0xffffffffu, tid >> 7, 0);
  const int wp = __shfl_sync(0xffffffffu, (tid >> 5) & 3, 0);
  const int lane = tid & 31;
  const int b = blockIdx.x, nb = gridDim.x;
  const int nfull = kNWIN / nb;
  if (tid == 0) {
    if ((sb & 1023) || nfull < 8) __trap();
#pragma unroll
    for (int i = 0; i < 4; i++) {
      mbar_init(sb + kOffBar + i * 8, 4);
      mbar_init(sb + kOffBar + 32 + i * 8, 7);
      mbar_init(sb + kOffBarB + i * 8, 7);
    }
    asm volatile("st.shared.v4.b32 [%0], {%1,%1,%1,%1};" ::"r"(sb + kOffFlag), "r"(0) : "memory");
    mbar_init(sb + kOffBarW, 1); mbar_init(sb + kOffBarW + 8, 1);
    asm volatile("fence.mbarrier_init.release.cluster;" ::: "memory");
  }
  if (tid >= 128 && tid < 488) {
    const uint32_t e = tid - 128, fr = min(e / 20, 15u);
    asm volatile("st.shared.v4.b32 [%0], {%1,%1,%1,%1};" ::"r"(sb + kOffBuf + fr * kFrame + kXBytes + (e - fr * 20) * 16), "r"(e - fr * 20 < 16 ? kPadStat : 0u) : "memory");
    asm volatile("fence.proxy.async.shared::cta;" ::: "memory");
  }
#pragma unroll
  for (int i = 0; i < PAD; i++) sched_fence(tid + i, 0, 0);
  __syncthreads();
  if (lane == 0 && wg < 2) tma_load(sb + kOffBuf + (tid >> 5) * kFrame, &tm, sb + kOffBar + wg * 8, b + wg * nb, wp);
  __syncwarp();
  asm volatile("griddepcontrol.wait;" ::: "memory");
  if (tid == 0) {
    if (!(WF & 1)) asm volatile("fence.proxy.async.global;" ::: "memory");
#pragma unroll
    for (int i = 0; i < 2; i++) {
      const uint32_t o = i ? kOffAs : 0, n = i ? kWBytes - kOffAs : kOffAs, bar = sb + kOffBarW + 8 * i;
      mbar_expect(bar, n);
      asm volatile("cp.async.bulk.shared::cluster.global.mbarrier::complete_tx::bytes [%0], [%1], %2, [%3];"
                   ::"r"(sb + o), "l"(reinterpret_cast<const uint8_t*>(g_wimg) + o), "r"(n), "r"(bar) : "memory");
    }
  }
  __syncwarp();
  if (wg >= 2) {
    if (WS) mbar_wait(sb + kOffBarW + (WS == 2 || (WS == 3 && wg == 3) ? 8 : 0), 0);
    if (lane == 0) tma_load(sb + kOffBuf + (tid >> 5) * kFrame, &tm, sb + kOffBar + wg * 8, b + wg * nb, wp);
    __syncwarp();
  }
  Params P;
  {
    const float4 p0 = __ldcg(reinterpret_cast<const float4*>(&g_par));
    P.cS_t = p0.x; P.cS_s = p0.y; P.kt = p0.z; P.kappa = p0.w;
    P.sgmin = fmaxf(0.0045f, P.kappa * 0.011f);
  }
  const bool scaled = __any_sync(0xffffffffu, P.cS_s != 1.f);
  const bool direct = __all_sync(0xffffffffu, (P.cS_t == 1.f) & (P.kt <= 256.f) & (P.kappa <= 16.f));
  const int widx = __popc(((ROLE >> wg) & 1 ? ROLE : ~ROLE) & ((1 << wg) - 1));
  const bool isT = (ROLE >> wg) & 1;
  if (isT) {
    loop_T(sb, nfull, widx, wp, lane, P, direct TRPASS(g_trace + (b * 16 + wg * 4 + wp) * 1024));
  } else {
    loop_S(sb, nfull, widx, wp, lane, P, scaled, &tm, out TRPASS(g_trace + (b * 16 + wg * 4 + wp) * 1024));
  }
}

__device__ __forceinline__ int ch_pos(int ch) { return 32 * (ch >> 5) + 4 * (ch & 4) + 8 * (ch & 1) + 2 * ((ch >> 3) & 3) + ((ch >> 1) & 1); }
__device__ __forceinline__ float pow2_ceil(float v) {
  return __uint_as_float((__float_as_uint(v) + 0x7fffffu) & 0x7f800000u);
}

constexpr int kPrepSplit = 12;
constexpr int kPrepThreads = 384;
__global__ void __launch_bounds__(kPrepThreads) swin_prep(const __nv_bfloat16* __restrict__ wqkv_t, const __nv_bfloat16* __restrict__ wo_t,
                                                          const __nv_bfloat16* __restrict__ wqkv_s, const __nv_bfloat16* __restrict__ wo_s) {
  asm volatile("griddepcontrol.launch_dependents;");
  if (blockIdx.x == 0 && threadIdx.x == 0) g_ctr = 0;
  __shared__ __align__(16) uint32_t raw[2][96][52];
  __shared__ __align__(16) uint32_t mu[3][52];
  __shared__ float nrm[12], nrm2[6], csum[6][9];
  const int mat = blockIdx.x / kPrepSplit, blk = blockIdx.x % kPrepSplit;
  const int tid = threadIdx.x, lane = tid & 31, warp = tid >> 5, g = lane >> 2, c = lane & 3;
  const __nv_bfloat16* wqkv = mat < 2 ? wqkv_t : wqkv_s;
  const __nv_bfloat16* wo = mat < 2 ? wo_t : wo_s;
  const bool isA = (mat & 1) == 0;
  {
    uint4 v[3], u[3];
#pragma unroll
    for (int q = 0; q < 3; q++) {
      const int e = tid + q * kPrepThreads, i = e / 12, c8 = (e % 12) * 8;
      v[q] = __ldg(reinterpret_cast<const uint4*>(wqkv + i * 288 + (isA ? 0 : 192) + c8));
      u[q] = __ldg(reinterpret_cast<const uint4*>(isA ? wqkv + i * 288 + 96 + c8 : wo + i * 96 + c8));
    }
#pragma unroll
    for (int q = 0; q < 3; q++) {
      const int e = tid + q * kPrepThreads, i = e / 12, c4 = (e % 12) * 4;
      *reinterpret_cast<uint4*>(&raw[0][i][c4]) = v[q];
      *reinterpret_cast<uint4*>(&raw[1][i][c4]) = u[q];
    }
  }
  __syncthreads();
  {
    const int m = warp / 6, cp = (warp % 6) * 8 + g;
    float s0 = 0.f, s1 = 0.f, q0 = 0.f, q1 = 0.f;
#pragma unroll
    for (int i = 0; i < 24; i++) {
      const uint32_t w = raw[m][4 * i + c][cp];
      const float lo = __uint_as_float(w << 16), hi = __uint_as_float(w & 0xffff0000u);
      s0 += lo; s1 += hi; q0 = fmaf(lo, lo, q0); q1 = fmaf(hi, hi, q1);
    }
    s0 = quad_sum(s0) * (1.f / 96.f); s1 = quad_sum(s1) * (1.f / 96.f); q0 = quad_sum(q0); q1 = quad_sum(q1);
    if (mat == 1 && m == 1) {
      float r0 = 0.f, r1 = 0.f;
#pragma unroll
      for (int i = 0; i < 12; i++) {
        const uint32_t w0 = raw[1][2 * cp][4 * i + c], w1 = raw[1][2 * cp + 1][4 * i + c];
        r0 += __uint_as_float(w0 << 16) + __uint_as_float(w0 & 0xffff0000u);
        r1 += __uint_as_float(w1 << 16) + __uint_as_float(w1 & 0xffff0000u);
      }
      r0 = quad_sum(r0) * (1.f / 96.f); r1 = quad_sum(r1) * (1.f / 96.f);
      s0 = r0; s1 = r1;
    }
    if (m == 1 && c == 0) {
      const uint32_t hi = mat == 3 ? 0u : pack_bf2(s0, s1);
      mu[0][cp] = hi;
      mu[1][cp] = mat == 3 ? 0u : pack_bf2(s0 - __uint_as_float(hi << 16), s1 - __uint_as_float(hi & 0xffff0000u));
      mu[2][cp] = 0u;
    }
    if (m == 0 || isA) {
      q0 = fmaxf(fmaf(-96.f * s0, s0, q0), 0.f) + q0 * 1e-6f;
      q1 = fmaxf(fmaf(-96.f * s1, s1, q1), 0.f) + q1 * 1e-6f;
    }
    const bool usemax = m == 1 && mat == 3;
    float t = usemax ? fmaxf(q0, q1) : q0 + q1;
#pragma unroll
    for (int o = 4; o < 32; o <<= 1) { const float z = __shfl_xor_sync(0xffffffffu, t, o); t = usemax ? fmaxf(t, z) : t + z; }
    if (lane == 0) nrm[warp] = t;
  }
  __syncthreads();
  if (warp >= 6) return;
  float d[4] = {0.f, 0.f, 0.f, 0.f}, e[4] = {0.f, 0.f, 0.f, 0.f}, v0, v1;
  {
    const uint32_t arow = smem_u32(&raw[0][16 * warp + (lane & 15)][(lane >> 4) * 4]);
    const uint32_t brow = isA ? smem_u32(&raw[1][blk * 8 + (lane & 7)][(lane >> 3) * 4]) : smem_u32(&raw[1][lane][blk * 4]);
    const uint32_t mrow = smem_u32(&mu[min(lane & 7, 2)][(lane >> 3) * 4]);
#pragma unroll
    for (int k2 = 0; k2 < 3; k2++) {
      uint32_t b[4], m[4];
      if (isA) ldsm4(b, brow + k2 * 64);
      else asm volatile("ldmatrix.sync.aligned.m8n8.x4.trans.shared.b16 {%0,%1,%2,%3}, [%4];"
                        : "=r"(b[0]), "=r"(b[1]), "=r"(b[2]), "=r"(b[3]) : "r"(brow + k2 * (32 * 208)) : "memory");
      ldsm4(m, mrow + k2 * 64);
#pragma unroll
      for (int hf = 0; hf < 2; hf++) {
        uint32_t a[4];
        ldsm4(a, arow + (2 * k2 + hf) * 32);
        asm volatile("mma.sync.aligned.m16n8k16.row.col.f32.bf16.bf16.f32 {%0,%1,%2,%3},{%4,%5,%6,%7},{%8,%9},{%0,%1,%2,%3};"
                     : "+f"(d[0]), "+f"(d[1]), "+f"(d[2]), "+f"(d[3])
                     : "r"(a[0]), "r"(a[1]), "r"(a[2]), "r"(a[3]), "r"(b[2 * hf]), "r"(b[2 * hf + 1]));
        asm volatile("mma.sync.aligned.m16n8k16.row.col.f32.bf16.bf16.f32 {%0,%1,%2,%3},{%4,%5,%6,%7},{%8,%9},{%0,%1,%2,%3};"
                     : "+f"(e[0]), "+f"(e[1]), "+f"(e[2]), "+f"(e[3])
                     : "r"(a[0]), "r"(a[1]), "r"(a[2]), "r"(a[3]), "r"(m[2 * hf]), "r"(m[2 * hf + 1]));
      }
    }
    v0 = __shfl_sync(0xffffffffu, e[0] + e[1], lane & ~3); v1 = __shfl_sync(0xffffffffu, e[2] + e[3], lane & ~3);
    d[0] -= v0; d[1] -= v0; d[2] -= v1; d[3] -= v1;
    float t0 = d[0] + d[2], t1 = d[1] + d[3], t2 = v0 + v1;
#pragma unroll
    for (int o = 4; o < 32; o <<= 1) {
      t0 += __shfl_xor_sync(0xffffffffu, t0, o); t1 += __shfl_xor_sync(0xffffffffu, t1, o); t2 += __shfl_xor_sync(0xffffffffu, t2, o);
    }
    if (g == 0) { csum[warp][2 * c] = t0; csum[warp][2 * c + 1] = t1; csum[warp][8] = t2; }
  }
  const float nl = nrm[0] + nrm[1] + nrm[2] + nrm[3] + nrm[4] + nrm[5];
  const float nr = mat == 3 ? fmaxf(fmaxf(fmaxf(nrm[6], nrm[7]), fmaxf(nrm[8], nrm[9])), fmaxf(nrm[10], nrm[11]))
                            : nrm[6] + nrm[7] + nrm[8] + nrm[9] + nrm[10] + nrm[11];
  const float bound = __fsqrt_rn(nl) * __fsqrt_rn(nr) * 1.01f;
  const float f = isA ? 0.14724448f : 1.f;
  float sc = pow2_ceil(fmaxf(bound * (isA ? 0.14724448f / 160.f : mat == 1 ? 1.f / 16.f : 1.f / 64.f), 1e-30f));
  if (isA) sc = fminf(fmaxf(sc, 1.f), 32768.f);
  const float mul = f * __uint_as_float(0x7f000000u - __float_as_uint(sc));
  if (blk == 0 && tid == 0) (mat == 0 ? g_par.cS_t : mat == 1 ? g_par.kt : mat == 2 ? g_par.cS_s : g_par.kappa) = sc;
  asm volatile("bar.sync 1, 192;" ::: "memory");
  float mean[2];
#pragma unroll
  for (int b = 0; b < 2; b++)
    mean[b] = (csum[0][2 * c + b] + csum[1][2 * c + b] + csum[2][2 * c + b] + csum[3][2 * c + b] + csum[4][2 * c + b] + csum[5][2 * c + b]) *
              (1.f / 96.f);
  uint8_t* img = reinterpret_cast<uint8_t*>(g_wimg) + (mat == 0 ? 0 : mat == 1 ? kOffWt : mat == 2 ? kOffAs : kOffWs);
  const float vmean = (csum[0][8] + csum[1][8] + csum[2][8] + csum[3][8] + csum[4][8] + csum[5][8]) * (1.f / 96.f);
  float off = 0.f;
  if (mat == 2) {
    float q2 = 0.f;
#pragma unroll
    for (int q = 0; q < 4; q++) q2 = fmaf(d[q] - mean[q & 1], d[q] - mean[q & 1], q2);
#pragma unroll
    for (int o = 16; o; o >>= 1) q2 += __shfl_xor_sync(0xffffffffu, q2, o);
    if (lane == 0) nrm2[warp] = q2;
    asm volatile("bar.sync 1, 192;" ::: "memory");
    q2 = nrm2[0] + nrm2[1] + nrm2[2] + nrm2[3] + nrm2[4] + nrm2[5];
    off = 1.5f * pow2_ceil(fmaxf(__fsqrt_rn(q2 * (1.f / 768.f)) * mul * 3.f, 1e-4f));
  }
#pragma unroll
  for (int q = 0; q < 4; q++) {
    const int kp = ch_pos(16 * warp + g + 8 * (q >> 1)), np = ch_pos(blk * 8 + 2 * c + (q & 1));
    const uint32_t ko = (kp >> 5) * (mat == 0 ? kAtChunk : 6144) + (kp & 31) * 2;
    uint32_t a = ko + np * 64;
    a ^= ((a >> 7) & 3) << 4;
    float o = (d[q] - mean[q & 1]) * mul;
    o = mat == 2 ? o + off : __uint_as_float((__float_as_uint(o) + 0x8000u) & 0xffff0000u);
    *reinterpret_cast<__half*>(img + a) = __float2half_rn(o);
    if (mat == 1 && blk == 0) {
      a = (kp >> 5) * kAtChunk + (kp & 31) * 2 + (96 + 2 * c + (q & 1)) * 64;
      a ^= ((a >> 7) & 3) << 4;
      *reinterpret_cast<__half*>(reinterpret_cast<uint8_t*>(g_wimg) + a) = __float2half_rn((q & 1) ? ((q >> 1 ? v1 : v0) - vmean) * mul : 1.f / 96.f);
    }
  }
}

typedef CUresult (*EncodeFn)(CUtensorMap*, CUtensorMapDataType, cuuint32_t, void*, const cuuint64_t*, const cuuint64_t*,
                             const cuuint32_t*, const cuuint32_t*, CUtensorMapInterleave, CUtensorMapSwizzle,
                             CUtensorMapL2promotion, CUtensorMapFloatOOBfill);

}

extern "C" void kernel_launch(void* const* d_in, const int* in_sizes, int n_in, void* d_out, int out_size) {
  (void)in_sizes; (void)n_in; (void)out_size;
  static EncodeFn enc = nullptr;
  static int nsm = 0;
  if (!enc) {
    void* fn = nullptr;
    cudaDriverEntryPointQueryResult qr;
    cudaGetDriverEntryPoint("cuTensorMapEncodeTiled", &fn, cudaEnableDefault, &qr);
    enc = reinterpret_cast<EncodeFn>(fn);
    int dev = 0;
    cudaGetDevice(&dev);
    cudaDeviceGetAttribute(&nsm, cudaDevAttrMultiProcessorCount, dev);
    cudaFuncSetAttribute(swin_main, cudaFuncAttributeMaxDynamicSharedMemorySize, kSmemBytes);
  }
  Maps maps;
  CUtensorMap& tm = maps.tm;
  const cuuint64_t dims[5] = {32, kW, kH, kT, 3};
  const cuuint64_t strides[4] = {192, 192ull * kW, 192ull * kW * kH, 64};
  const cuuint32_t box[5] = {32, 7, 7, 1, 3};
  const cuuint32_t es[5] = {1, 1, 1, 1, 1};
  enc(&tm, CU_TENSOR_MAP_DATA_TYPE_BFLOAT16, 5, d_in[0], dims, strides, box, es, CU_TENSOR_MAP_INTERLEAVE_NONE,
      CU_TENSOR_MAP_SWIZZLE_64B, CU_TENSOR_MAP_L2_PROMOTION_L2_128B, CU_TENSOR_MAP_FLOAT_OOB_FILL_NONE);
  {
    const cuuint64_t d3[3] = {24 * kW, kH, kT};
    const cuuint64_t s3[2] = {192ull * kW, 192ull * kW * kH};
    const cuuint32_t b3[3] = {168, 7, 1};
    enc(&maps.pf, CU_TENSOR_MAP_DATA_TYPE_INT64, 3, d_in[0], d3, s3, b3, es, CU_TENSOR_MAP_INTERLEAVE_NONE,
        CU_TENSOR_MAP_SWIZZLE_NONE, (CUtensorMapL2promotion)PRM, CU_TENSOR_MAP_FLOAT_OOB_FILL_NONE);
  }

  cudaStream_t st = cudaStreamPerThread;
  swin_prep<<<4 * kPrepSplit, kPrepThreads, 0, st>>>(
      static_cast<const __nv_bfloat16*>(d_in[1]), static_cast<const __nv_bfloat16*>(d_in[2]),
      static_cast<const __nv_bfloat16*>(d_in[3]), static_cast<const __nv_bfloat16*>(d_in[4]));

  cudaLaunchConfig_t cfg = {};
  cfg.gridDim = dim3(nsm);
  cfg.blockDim = dim3(kNWG * 128);
  cfg.dynamicSmemBytes = kSmemBytes;
  cfg.stream = st;
  cudaLaunchAttribute at[1];
  at[0].id = cudaLaunchAttributeProgrammaticStreamSerialization;
  at[0].val.programmaticStreamSerializationAllowed = 1;
  cfg.attrs = at;
  cfg.numAttrs = 1;
  cudaLaunchKernelEx(&cfg, swin_main, maps, static_cast<uint8_t*>(d_out));
}
```

```cpp
#include <cuda_runtime.h>
#include <cuda.h>
#include <cuda_bf16.h>
#include <cuda_fp16.h>
#include <stdint.h>

#define LB 512
#define SF 17
#define TIE 0
#define SG 1
#define IL 1
#define FP 2
#define ROLE 3
#define RF 2
#define CK0 0
#define LIKELY(x) __builtin_expect(!!(x), 1)
#define UNLIKELY(x) __builtin_expect(!!(x), 0)
#define CV 1
#define C1 2
#define C2 1
#define WS 2
#define TL 1
#define PAD 0
#define SPL 1
#define SPN 64
#define SPO 1
#define LD 1
#define DA 1
#define E1 0
#define E2 0
#define E3 0
#define E4 0
#define G4 0
#define BE 0
#define CS 0
#define QP 3
#define PG 1
#define PR 4
#define PF0 1
#define EARLY 0
#define PF 2
#define HQ 1
#define PRM 2
#define CM 0
#define AB 0
#define ST 0
#define WF 1
#define NWH 25
#define DYN 1
#define EL 0
#define HD 0
#define OA 3
#define OB 1
#define OC 1
#define OH 1
#define XE 0
#define XP 0
#define XN 24
#define LP0 0
#define LP1 0
#define R1 1
#define SM 3
#define Q1 0
#define LA 4
#define LB2 4
#define LF 0
#define GB 0
#define GL 6
#define SQA 0
#define R2 0
#define R3 1
#define R4x 1
#define W1x 1
#define K1 1
#define S1 1
#define PU 0
#define TH 0
#define SB0 0
#define PL 0
#define WP 0
#define W0 2
#define W1e 2
#define PP 7
namespace {

constexpr int kH = 511, kW = 511, kT = 4;
constexpr int kNWX = 73, kNWIN = 73 * 73;
constexpr int kChunk = 3136;
constexpr int kXBytes = 3 * kChunk;
constexpr int kFrame = 9728;
constexpr int kBufStride = 4 * kFrame;
constexpr uint32_t kPadStat = 0x7bff;
constexpr int kWMat = 18432;
constexpr int kAtChunk = 104 * 64;
constexpr int kOffWt = 3 * kAtChunk;
constexpr int kOffAs = kOffWt + kWMat, kOffWs = kOffAs + kWMat;
constexpr int kWBytes = kOffWs + kWMat;
constexpr int kOffBuf = kWBytes;
constexpr int kOffBar = kOffBuf + 4 * kBufStride + 640;
constexpr int kOffFlag = kOffBar + 64;
constexpr int kOffBarW = kOffBar + 80;
constexpr int kOffBarB = kOffBar + 96;
constexpr int kOffCs = kOffBar + 128;
constexpr int kOffClaim = kOffBar + 132;
constexpr int kSmemBytes = kOffBar + 144;
constexpr int kNWG = 4;

struct Maps { CUtensorMap tm, pf; };
struct Params {
  float cS_t, cS_s;
  float kt;
  float kappa;
  float sgmin;
};

__device__ uint4 g_wimg[kWBytes / 16];
__device__ __align__(16) Params g_par;
__device__ uint32_t g_ctr;

#define TR(idx)
#define TRARG
#define TRPASS(x)
__device__ __forceinline__ uint32_t smem_u32(const void* p) { return (uint32_t)__cvta_generic_to_shared(p); }
__device__ __forceinline__ void mbar_init(uint32_t a, int c) { asm volatile("mbarrier.init.shared::cta.b64 [%0], %1;" ::"r"(a), "r"(c)); }
__device__ __forceinline__ void mbar_expect(uint32_t a, int bytes) {
  asm volatile("mbarrier.arrive.expect_tx.shared::cta.b64 _, [%0], %1;" ::"r"(a), "r"(bytes) : "memory");
}
__device__ __forceinline__ void mbar_arrive(uint32_t a) {
  asm volatile("mbarrier.arrive.shared::cta.b64 _, [%0];" ::"r"(a) : "memory");
}
__device__ __forceinline__ void mbar_wait(uint32_t a, uint32_t par) {
  asm volatile(
      "{\n.reg .pred p;\n.reg .u32 n;\n"
      "mbarrier.try_wait.parity.shared::cta.b64 p, [%0], %1;\n"
      "@p bra.uni WDONE;\n"
      "mov.u32 n, 0;\n"
      "WLOOP:\n"
      "mbarrier.try_wait.parity.shared::cta.b64 p, [%0], %1;\n"
      "@p bra.uni WDONE;\n"
      "add.u32 n, n, 1;\n"
      "setp.lt.u32 p, n, 0x1000000;\n"
      "@p bra.uni WLOOP;\n"
      "trap;\n"
      "WDONE:\n}" ::"r"(a), "r"(par), "n"(TH) : "memory");
}
__device__ __forceinline__ void tma_load(uint32_t dst, const CUtensorMap* m, uint32_t bar, uint32_t w, uint32_t t) {
  const uint32_t wy = (w * 57457u) >> 22, wx = w - wy * kNWX;
  mbar_expect(bar, kXBytes);
  asm volatile(
      "cp.async.bulk.tensor.5d.shared::cluster.global.mbarrier::complete_tx::bytes [%0], [%1, {%3,%4,%5,%6,%3}], [%2];" ::"r"(dst),
      "l"(m), "r"(bar), "r"(0), "r"(wx * 7), "r"(wy * 7), "r"(t)
      : "memory");
}
__device__ __forceinline__ void tma_prefetch(const CUtensorMap* m, uint32_t w, uint32_t t) {
  const uint32_t wy = (w * 57457u) >> 22, wx = w - wy * kNWX;
  asm volatile("cp.async.bulk.prefetch.tensor.3d.L2.global [%0, {%1,%2,%3}];" ::"l"(m + 1), "r"(wx * 168), "r"(wy * 7), "r"(t) : "memory");
}
template <bool kPrefetch>
__device__ __forceinline__ void tma_load_elect(uint32_t dst, const CUtensorMap* m, uint32_t bar, uint32_t w, uint32_t t, uint32_t tp) {
  const uint32_t wy = (w * 57457u) >> 22, wx = w - wy * kNWX;
  asm volatile("{\n.reg .pred p;\nelect.sync _|p, 0xffffffff;\n"
               "@p mbarrier.arrive.expect_tx.shared::cta.b64 _, [%2], %7;\n"
               "@p cp.async.bulk.tensor.5d.shared::cluster.global.mbarrier::complete_tx::bytes [%0], [%1, {%3,%4,%5,%6,%3}], [%2];\n}"
               ::"r"(dst), "l"(m), "r"(bar), "r"(0), "r"(wx * 7), "r"(wy * 7), "r"(t), "n"(kXBytes) : "memory");
  if (kPrefetch)
    asm volatile("{\n.reg .pred p;\nelect.sync _|p, 0xffffffff;\n@p cp.async.bulk.prefetch.tensor.3d.L2.global [%0, {%1,%2,%3}];\n}"
                 ::"l"(m + 1), "r"(wx * 168), "r"(wy * 7), "r"(tp) : "memory");
}
__device__ __forceinline__ void wg_fence() { asm volatile("wgmma.fence.sync.aligned;" ::: "memory"); }
__device__ __forceinline__ void wg_commit() { asm volatile("wgmma.commit_group.sync.aligned;" ::: "memory"); }
template <int N>
__device__ __forceinline__ void wg_wait() { asm volatile("wgmma.wait_group.sync.aligned %0;" ::"n"(N) : "memory"); }
template <int N>
__device__ __forceinline__ void pin(uint32_t* d) {
#pragma unroll
  for (int i = 0; i < N; i++) asm volatile("" : "+r"(d[i])::"memory");
}
__device__ __forceinline__ void sched_fence(uint32_t a, uint32_t b, uint32_t c) {
  asm volatile("{\n.reg .pred p;\n.reg .b32 t;\nsetp.ne.u32 p, %0, 0x7fffffff;\n@p bra.uni SFD;\n"
               "add.u32 t, %1, %2;\nadd.u32 t, t, %3;\nnanosleep.u32 t;\nSFD:\n}" ::"r"(gridDim.x), "r"(a), "r"(b), "r"(c) : "memory");
}
__device__ __forceinline__ void hold(uint32_t sb, uint32_t v) {
  asm volatile("{\n.reg .pred p;\nsetp.eq.u32 p, %0, 0x7fffffff;\n@p st.volatile.shared.b32 [%1], %2;\n}" ::"r"(gridDim.x), "r"(sb), "r"(v) : "memory");
}
__device__ __forceinline__ uint64_t mk_desc(uint32_t addr, uint32_t lbo16) {
  return ((uint64_t)0x80000020u << 32) | ((addr >> 4) & 0x3fff) | (lbo16 << 16);
}

__device__ __forceinline__ uint64_t desc_at(uint32_t lo) { return ((uint64_t)0x80000020u << 32) | lo; }

#define R4(d, i) "+r"(d[i]), "+r"(d[i + 1]), "+r"(d[i + 2]), "+r"(d[i + 3])
#define O4(d, i) "=r"(d[i]), "=r"(d[i + 1]), "=r"(d[i + 2]), "=r"(d[i + 3])
#define D24 "{%0,%1,%2,%3,%4,%5,%6,%7,%8,%9,%10,%11,%12,%13,%14,%15,%16,%17,%18,%19,%20,%21,%22,%23},"
#define D14 "{%0,%1,%2,%3,%4,%5,%6,%7,%8,%9,%10,%11,%12,%13},"

template <int SC, int TB>
__device__ __forceinline__ void wg96h(uint32_t (&d)[24], const uint32_t* a, uint64_t db, uint32_t acc = 0) {
  if (SC == 2)
    asm volatile("{\n.reg .pred p;\nsetp.ne.u32 p, %30, 0;\n"
                 "wgmma.mma_async.sync.aligned.m64n96k16.f16.f16.f16 " D24 "{%24,%25,%26,%27}, %28, p, 1, 1, %29;\n}"
                 : R4(d, 0), R4(d, 4), R4(d, 8), R4(d, 12), R4(d, 16), R4(d, 20)
                 : "r"(a[0]), "r"(a[1]), "r"(a[2]), "r"(a[3]), "l"(db), "n"(TB), "r"(acc));
  else if (SC)
    asm volatile("wgmma.mma_async.sync.aligned.m64n96k16.f16.f16.f16 " D24 "{%24,%25,%26,%27}, %28, 1, 1, 1, %29;"
                 : R4(d, 0), R4(d, 4), R4(d, 8), R4(d, 12), R4(d, 16), R4(d, 20)
                 : "r"(a[0]), "r"(a[1]), "r"(a[2]), "r"(a[3]), "l"(db), "n"(TB));
  else
    asm volatile("wgmma.mma_async.sync.aligned.m64n96k16.f16.f16.f16 " D24 "{%24,%25,%26,%27}, %28, 0, 1, 1, %29;"
                 : O4(d, 0), O4(d, 4), O4(d, 8), O4(d, 12), O4(d, 16), O4(d, 20)
                 : "r"(a[0]), "r"(a[1]), "r"(a[2]), "r"(a[3]), "l"(db), "n"(TB));
}
template <int SC>
__device__ __forceinline__ void wg104h(uint32_t (&d)[26], const uint32_t* a, uint64_t db) {
  if (SC)
    asm volatile("wgmma.mma_async.sync.aligned.m64n104k16.f16.f16.f16 "
                 "{%0,%1,%2,%3,%4,%5,%6,%7,%8,%9,%10,%11,%12,%13,%14,%15,%16,%17,%18,%19,%20,%21,%22,%23,%24,%25},"
                 "{%26,%27,%28,%29}, %30, 1, 1, 1, 0;"
                 : R4(d, 0), R4(d, 4), R4(d, 8), R4(d, 12), R4(d, 16), R4(d, 20), "+r"(d[24]), "+r"(d[25])
                 : "r"(a[0]), "r"(a[1]), "r"(a[2]), "r"(a[3]), "l"(db));
  else
    asm volatile("wgmma.mma_async.sync.aligned.m64n104k16.f16.f16.f16 "
                 "{%0,%1,%2,%3,%4,%5,%6,%7,%8,%9,%10,%11,%12,%13,%14,%15,%16,%17,%18,%19,%20,%21,%22,%23,%24,%25},"
                 "{%26,%27,%28,%29}, %30, 0, 1, 1, 0;"
                 : O4(d, 0), O4(d, 4), O4(d, 8), O4(d, 12), O4(d, 16), O4(d, 20), "=r"(d[24]), "=r"(d[25])
                 : "r"(a[0]), "r"(a[1]), "r"(a[2]), "r"(a[3]), "l"(db));
}
template <int SC>
__device__ __forceinline__ void wg56h(uint32_t* d, const uint32_t* a, uint64_t db) {
  if (SC)
    asm volatile("wgmma.mma_async.sync.aligned.m64n56k16.f16.f16.f16 " D14 "{%14,%15,%16,%17}, %18, 1, 1, 1, 0;"
                 : R4(d, 0), R4(d, 4), R4(d, 8), "+r"(d[12]), "+r"(d[13])
                 : "r"(a[0]), "r"(a[1]), "r"(a[2]), "r"(a[3]), "l"(db));
  else
    asm volatile("wgmma.mma_async.sync.aligned.m64n56k16.f16.f16.f16 " D14 "{%14,%15,%16,%17}, %18, 0, 1, 1, 0;"
                 : O4(d, 0), O4(d, 4), O4(d, 8), "=r"(d[12]), "=r"(d[13])
                 : "r"(a[0]), "r"(a[1]), "r"(a[2]), "r"(a[3]), "l"(db));
}
template <int SC>
__device__ __forceinline__ void gemm_w(uint32_t (&d)[24], const uint32_t* a, uint64_t dw, uint32_t acc = 0) {
  wg_fence();
  wg96h<SC, 0>(d, a, dw, acc); wg96h<1, 0>(d, a + 4, dw + 2);
  wg96h<1, 0>(d, a + 8, dw + 384); wg96h<1, 0>(d, a + 12, dw + 386);
  wg96h<1, 0>(d, a + 16, dw + 768); wg96h<1, 0>(d, a + 20, dw + 770);
  wg_commit();
}
__device__ __forceinline__ void lds128(uint32_t* r, uint32_t a) {
  if (AB & 16) { asm volatile("ld.shared.b32 %0, [%1];" : "=r"(r[0]) : "r"(a) : "memory"); r[1] = r[0] + 0x10001; r[2] = r[0] ^ 0x80008000; r[3] = r[1] ^ 0x80008000; return; }
  asm volatile("ld.shared.v4.b32 {%0,%1,%2,%3}, [%4];" : "=r"(r[0]), "=r"(r[1]), "=r"(r[2]), "=r"(r[3]) : "r"(a) : "memory");
}
__device__ __forceinline__ uint32_t lds32(uint32_t a) {
  uint32_t r; asm volatile("ld.volatile.shared.b32 %0, [%1];" : "=r"(r) : "r"(a) : "memory"); return r;
}
__device__ __forceinline__ void sts32(uint32_t a, uint32_t v) { asm volatile("st.volatile.shared.b32 [%0], %1;" ::"r"(a), "r"(v) : "memory"); }
__device__ __forceinline__ void ldsm4x(uint32_t* r, uint32_t a) {
  asm volatile("ldmatrix.sync.aligned.m8n8.x1.shared.b16 {%0}, [%1];" : "=r"(r[0]) : "r"(a) : "memory");
  asm volatile("mov.b32 %0, %3;\nmov.b32 %1, %3;\nmov.b32 %2, %3;" : "=r"(r[1]), "=r"(r[2]), "=r"(r[3]) : "r"(r[0]));
}
__device__ __forceinline__ void ldsm4(uint32_t* r, uint32_t a) {
  asm volatile("ldmatrix.sync.aligned.m8n8.x4.shared.b16 {%0,%1,%2,%3}, [%4];"
               : "=r"(r[0]), "=r"(r[1]), "=r"(r[2]), "=r"(r[3]) : "r"(a) : "memory");
}
__device__ __forceinline__ void stsm4(uint32_t a, const uint32_t* r) {
  asm volatile("stmatrix.sync.aligned.m8n8.x4.shared.b16 [%0], {%1,%2,%3,%4};" ::"r"(a), "r"(r[0]), "r"(r[1]), "r"(r[2]), "r"(r[3])
               : "memory");
}
__device__ __forceinline__ uint32_t pack_h2(float lo, float hi) {
  uint32_t r; asm("cvt.rn.f16x2.f32 %0, %1, %2;" : "=r"(r) : "f"(hi), "f"(lo)); return r;
}
__device__ __forceinline__ uint32_t pack_h2_rz(float lo, float hi) {
  uint32_t r; asm("cvt.rz.f16x2.f32 %0, %1, %2;" : "=r"(r) : "f"(hi), "f"(lo)); return r;
}
__device__ __forceinline__ uint32_t pack_h2_sat(float lo, float hi) {
  uint32_t r; asm("cvt.rn.satfinite.f16x2.f32 %0, %1, %2;" : "=r"(r) : "f"(hi), "f"(lo)); return r;
}
__device__ __forceinline__ uint32_t pack_bf2(float lo, float hi) {
  uint32_t r; asm("cvt.rn.bf16x2.f32 %0, %1, %2;" : "=r"(r) : "f"(hi), "f"(lo)); return r;
}
__device__ __forceinline__ __half2 as_h2(uint32_t v) { return *reinterpret_cast<__half2*>(&v); }
__device__ __forceinline__ uint32_t as_u(__half2 v) { return *reinterpret_cast<uint32_t*>(&v); }
__device__ __forceinline__ float2 unpack_h2(uint32_t v) { return __half22float2(as_h2(v)); }
__device__ __forceinline__ uint32_t h2ex2(uint32_t v) { uint32_t r; asm("ex2.approx.f16x2 %0, %1;" : "=r"(r) : "r"(v)); return r; }
__device__ __forceinline__ uint32_t h2max(uint32_t a, uint32_t b) { return as_u(__hmax2(as_h2(a), as_h2(b))); }
__device__ __forceinline__ uint32_t h2add(uint32_t a, uint32_t b) { return as_u(__hadd2(as_h2(a), as_h2(b))); }
__device__ __forceinline__ uint32_t h2sub(uint32_t a, uint32_t b) { return as_u(__hsub2(as_h2(a), as_h2(b))); }
__device__ __forceinline__ uint32_t h2mul(uint32_t a, uint32_t b) { return as_u(__hmul2(as_h2(a), as_h2(b))); }
__device__ __forceinline__ uint32_t h2fma(uint32_t a, uint32_t b, uint32_t c) { return as_u(__hfma2(as_h2(a), as_h2(b), as_h2(c))); }
__device__ __forceinline__ uint32_t lo2(uint32_t v) { return as_u(__low2half2(as_h2(v))); }
__device__ __forceinline__ uint32_t hi2(uint32_t v) { return as_u(__high2half2(as_h2(v))); }
__device__ __forceinline__ uint32_t fold_add(uint32_t a, uint32_t b) { return h2add(__byte_perm(a, b, 0x5410), __byte_perm(a, b, 0x7632)); }
__device__ __forceinline__ uint32_t bitsel(uint32_t a, uint32_t m, uint32_t c) {
  uint32_t r; asm("lop3.b32 %0, %1, %2, %3, 0xe2;" : "=r"(r) : "r"(a), "r"(m), "r"(c)); return r;
}
__device__ __forceinline__ float rcp_fast(float v) { float r; asm("rcp.approx.ftz.f32 %0, %1;" : "=f"(r) : "f"(v)); return r; }
__device__ __forceinline__ float rsq_fast(float v) { float r; asm("rsqrt.approx.ftz.f32 %0, %1;" : "=f"(r) : "f"(v)); return r; }
__device__ __forceinline__ float quad_sum(float v) {
  v += __shfl_xor_sync(0xffffffffu, v, 1);
  return v + __shfl_xor_sync(0xffffffffu, v, 2);
}
__device__ __forceinline__ uint32_t quad_h2add(uint32_t v) {
  if (Q1) return h2add(h2add(v, __shfl_xor_sync(0xffffffffu, v, 1)), h2add(__shfl_xor_sync(0xffffffffu, v, 2), __shfl_xor_sync(0xffffffffu, v, 3)));
  v = h2add(v, __shfl_xor_sync(0xffffffffu, v, 1));
  return h2add(v, __shfl_xor_sync(0xffffffffu, v, 2));
}
__device__ __forceinline__ uint32_t score_scale(const float* p) { const float v = __ldcg(p); return pack_h2(v, v); }

constexpr float kEps96 = 1e-5f * 96.f * 96.f;
__device__ __forceinline__ float2 stat_f32(uint32_t e) {
  const float2 h = unpack_h2(e);
  return make_float2((e & 0x8000u) ? __uint_as_float((e << 16) & 0x7fff0000u) : h.x, (e & 0x8000u) ? __uint_as_float(e & 0xffff0000u) : h.y);
}

__device__ __forceinline__ uint32_t swz(uint32_t a) { return a ^ ((a >> 3) & 0x30); }
__device__ __forceinline__ uint32_t prmt(uint32_t a, uint32_t b, uint32_t s) {
  uint32_t r; asm("prmt.b32 %0, %1, %2, %3;" : "=r"(r) : "r"(a), "r"(b), "r"(s)); return r;
}
__device__ __forceinline__ void tie48(uint32_t* a, uint32_t* b, uint64_t d, uint32_t u = 0, uint32_t v = 0) {
  asm volatile("{\n.reg .pred p;\n.reg .b32 t;\nsetp.ne.u32 p, %48, 0x7fffffff;\n@p bra.uni TIED;\n"
               "wgmma.fence.sync.aligned;\n"
               "wgmma.mma_async.sync.aligned.m64n192k16.f16.f16.f16 {%0,%1,%2,%3,%4,%5,%6,%7,%8,%9,%10,%11,%12,%13,%14,%15,%16,%17,%18,%19,%20,%21,%22,%23,%24,%25,%26,%27,%28,%29,%30,%31,%32,%33,%34,%35,%36,%37,%38,%39,%40,%41,%42,%43,%44,%45,%46,%47}, %49, %49, 1, 1, 1, 0, 0;\n"
               "wgmma.commit_group.sync.aligned;\nwgmma.wait_group.sync.aligned 0;\nTIED:\n}"
               : R4(a, 0), R4(a, 4), R4(a, 8), R4(a, 12), R4(a, 16), R4(a, 20), R4(b, 0), R4(b, 4), R4(b, 8), R4(b, 12), R4(b, 16), R4(b, 20)
               : "r"(gridDim.x), "l"(d), "r"(u), "r"(v) : "memory");
}
template <int kPos>
__device__ __forceinline__ void x_work(uint32_t sb, uint32_t v) {
  if (XP != kPos) return;
  uint32_t a = v, b = v + 1, c = v + 2;
#pragma unroll
  for (int i = 0; i < XN / 3; i++)
    asm volatile("fma.rn.f16x2 %0, %0, %3, %3;\nfma.rn.f16x2 %1, %1, %3, %3;\nfma.rn.f16x2 %2, %2, %3, %3;" : "+r"(a), "+r"(b), "+r"(c) : "r"(v));
  hold(sb, a ^ b ^ c);
}
struct A3 { uint32_t a[3]; };
__device__ __forceinline__ A3 swz3(uint32_t a) { return A3{{swz(a), swz(a + kChunk), swz(a + 2 * kChunk)}}; }
__device__ __forceinline__ void load_row(uint32_t* x, const A3& a, int t) {
  lds128(x, a.a[0] + t * kFrame); lds128(x + 4, a.a[1] + t * kFrame); lds128(x + 8, a.a[2] + t * kFrame);
}
__device__ __forceinline__ void row_to_h2(uint32_t* y, const uint32_t* x) {
#pragma unroll
  for (int j = 0; j < 12; j += 2) {
    y[2 * j] = pack_h2(__uint_as_float(x[j] << 16), __uint_as_float(x[j + 1] << 16));
    uint32_t r;
    asm("cvt.rz.f16x2.f32 %0, %1, %2;" : "=r"(r) : "f"(__uint_as_float(x[j + 1])), "f"(__uint_as_float(x[j])));
    y[2 * j + 2] = r & 0xfff8fff8u;
  }
}
__device__ __forceinline__ void gemm_at(uint32_t (&q)[26], const uint32_t* z, uint64_t da) {
  wg_fence();
  wg104h<0>(q, z, da); wg104h<1>(q, z + 4, da + 2);
  wg104h<1>(q, z + 8, da + 416); wg104h<1>(q, z + 12, da + 418);
  wg104h<1>(q, z + 16, da + 832); wg104h<1>(q, z + 20, da + 834);
  wg_commit();
}
template <int SC>
__device__ __forceinline__ void wg64h(uint32_t* d, const uint32_t* a, uint64_t db) {
  if (SC)
    asm volatile("wgmma.mma_async.sync.aligned.m64n64k16.f16.f16.f16 {%0,%1,%2,%3,%4,%5,%6,%7,%8,%9,%10,%11,%12,%13,%14,%15}, {%16,%17,%18,%19}, %20, 1, 1, 1, 0;"
                 : "+r"(d[0]), "+r"(d[1]), "+r"(d[2]), "+r"(d[3]), "+r"(d[4]), "+r"(d[5]), "+r"(d[6]), "+r"(d[7]), "+r"(d[8]), "+r"(d[9]), "+r"(d[10]), "+r"(d[11]), "+r"(d[12]), "+r"(d[13]), "+r"(d[14]), "+r"(d[15])
                 : "r"(a[0]), "r"(a[1]), "r"(a[2]), "r"(a[3]), "l"(db));
  else
    asm volatile("wgmma.mma_async.sync.aligned.m64n64k16.f16.f16.f16 {%0,%1,%2,%3,%4,%5,%6,%7,%8,%9,%10,%11,%12,%13,%14,%15}, {%16,%17,%18,%19}, %20, 0, 1, 1, 0;"
                 : "=r"(d[0]), "=r"(d[1]), "=r"(d[2]), "=r"(d[3]), "=r"(d[4]), "=r"(d[5]), "=r"(d[6]), "=r"(d[7]), "=r"(d[8]), "=r"(d[9]), "=r"(d[10]), "=r"(d[11]), "=r"(d[12]), "=r"(d[13]), "=r"(d[14]), "=r"(d[15])
                 : "r"(a[0]), "r"(a[1]), "r"(a[2]), "r"(a[3]), "l"(db));
}
template <int SC>
__device__ __forceinline__ void wg40h(uint32_t* d, const uint32_t* a, uint64_t db) {
  if (SC)
    asm volatile("wgmma.mma_async.sync.aligned.m64n40k16.f16.f16.f16 {%0,%1,%2,%3,%4,%5,%6,%7,%8,%9}, {%10,%11,%12,%13}, %14, 1, 1, 1, 0;"
                 : "+r"(d[0]), "+r"(d[1]), "+r"(d[2]), "+r"(d[3]), "+r"(d[4]), "+r"(d[5]), "+r"(d[6]), "+r"(d[7]), "+r"(d[8]), "+r"(d[9])
                 : "r"(a[0]), "r"(a[1]), "r"(a[2]), "r"(a[3]), "l"(db));
  else
    asm volatile("wgmma.mma_async.sync.aligned.m64n40k16.f16.f16.f16 {%0,%1,%2,%3,%4,%5,%6,%7,%8,%9}, {%10,%11,%12,%13}, %14, 0, 1, 1, 0;"
                 : "=r"(d[0]), "=r"(d[1]), "=r"(d[2]), "=r"(d[3]), "=r"(d[4]), "=r"(d[5]), "=r"(d[6]), "=r"(d[7]), "=r"(d[8]), "=r"(d[9])
                 : "r"(a[0]), "r"(a[1]), "r"(a[2]), "r"(a[3]), "l"(db));
}
template <int SC>
__device__ __forceinline__ void wg80h(uint32_t* d, const uint32_t* a, uint64_t db) {
  if (SC)
    asm volatile("wgmma.mma_async.sync.aligned.m64n80k16.f16.f16.f16 {%0,%1,%2,%3,%4,%5,%6,%7,%8,%9,%10,%11,%12,%13,%14,%15,%16,%17,%18,%19}, {%20,%21,%22,%23}, %24, 1, 1, 1, 0;"
                 : "+r"(d[0]), "+r"(d[1]), "+r"(d[2]), "+r"(d[3]), "+r"(d[4]), "+r"(d[5]), "+r"(d[6]), "+r"(d[7]), "+r"(d[8]), "+r"(d[9]), "+r"(d[10]), "+r"(d[11]), "+r"(d[12]), "+r"(d[13]), "+r"(d[14]), "+r"(d[15]), "+r"(d[16]), "+r"(d[17]), "+r"(d[18]), "+r"(d[19])
                 : "r"(a[0]), "r"(a[1]), "r"(a[2]), "r"(a[3]), "l"(db));
  else
    asm volatile("wgmma.mma_async.sync.aligned.m64n80k16.f16.f16.f16 {%0,%1,%2,%3,%4,%5,%6,%7,%8,%9,%10,%11,%12,%13,%14,%15,%16,%17,%18,%19}, {%20,%21,%22,%23}, %24, 0, 1, 1, 0;"
                 : "=r"(d[0]), "=r"(d[1]), "=r"(d[2]), "=r"(d[3]), "=r"(d[4]), "=r"(d[5]), "=r"(d[6]), "=r"(d[7]), "=r"(d[8]), "=r"(d[9]), "=r"(d[10]), "=r"(d[11]), "=r"(d[12]), "=r"(d[13]), "=r"(d[14]), "=r"(d[15]), "=r"(d[16]), "=r"(d[17]), "=r"(d[18]), "=r"(d[19])
                 : "r"(a[0]), "r"(a[1]), "r"(a[2]), "r"(a[3]), "l"(db));
}
template <int SC>
__device__ __forceinline__ void wg24h(uint32_t* d, const uint32_t* a, uint64_t db) {
  if (SC)
    asm volatile("wgmma.mma_async.sync.aligned.m64n24k16.f16.f16.f16 {%0,%1,%2,%3,%4,%5}, {%6,%7,%8,%9}, %10, 1, 1, 1, 0;"
                 : "+r"(d[0]), "+r"(d[1]), "+r"(d[2]), "+r"(d[3]), "+r"(d[4]), "+r"(d[5])
                 : "r"(a[0]), "r"(a[1]), "r"(a[2]), "r"(a[3]), "l"(db));
  else
    asm volatile("wgmma.mma_async.sync.aligned.m64n24k16.f16.f16.f16 {%0,%1,%2,%3,%4,%5}, {%6,%7,%8,%9}, %10, 0, 1, 1, 0;"
                 : "=r"(d[0]), "=r"(d[1]), "=r"(d[2]), "=r"(d[3]), "=r"(d[4]), "=r"(d[5])
                 : "r"(a[0]), "r"(a[1]), "r"(a[2]), "r"(a[3]), "l"(db));
}
__device__ __forceinline__ void gemm_at2(uint32_t (&q)[26], const uint32_t* z, uint64_t da) {
  wg_fence();
#define WA wg64h
#define WB wg40h
  constexpr int o = SPN / 4, e = SPN * 4;
  WA<0>(q, z, da); WB<0>(q + o, z, da + e); WA<1>(q, z + 4, da + 2); WB<1>(q + o, z + 4, da + e + 2);
  WA<1>(q, z + 8, da + 416); WB<1>(q + o, z + 8, da + e + 416); WA<1>(q, z + 12, da + 418); WB<1>(q + o, z + 12, da + e + 418);
  WA<1>(q, z + 16, da + 832); WB<1>(q + o, z + 16, da + e + 832); WA<1>(q, z + 20, da + 834); WB<1>(q + o, z + 20, da + e + 834);
  wg_commit();
}
__device__ __forceinline__ void wg48h(uint32_t* d, const uint32_t* a, uint64_t db) {
  asm volatile("wgmma.mma_async.sync.aligned.m64n48k16.f16.f16.f16 {%0,%1,%2,%3,%4,%5,%6,%7,%8,%9,%10,%11}, {%12,%13,%14,%15}, %16, 1, 1, 1, 0;"
               : "+r"(d[0]), "+r"(d[1]), "+r"(d[2]), "+r"(d[3]), "+r"(d[4]), "+r"(d[5]), "+r"(d[6]), "+r"(d[7]), "+r"(d[8]), "+r"(d[9]), "+r"(d[10]), "+r"(d[11])
               : "r"(a[0]), "r"(a[1]), "r"(a[2]), "r"(a[3]), "l"(db));
}
__device__ __forceinline__ void gemm_w2(uint32_t* d, const uint32_t* a, uint64_t dw) {
  wg_fence();
#pragma unroll
  for (int k = 0; k < 6; k++) {
    wg48h(d, a + 4 * k, dw + (k >> 1) * 384 + (k & 1) * 2); wg48h(d + 12, a + 4 * k, dw + (k >> 1) * 384 + (k & 1) * 2 + 192);
  }
  wg_commit();
}
template <int kChains = 2>
__device__ __forceinline__ uint32_t sumsq(const uint32_t* z) {
  if (kChains == 1) {
    uint32_t a = h2mul(z[0], z[0]), b = h2mul(z[1], z[1]);
#pragma unroll
    for (int j = 1; j < 12; j++) { a = h2fma(z[2 * j], z[2 * j], a); b = h2fma(z[2 * j + 1], z[2 * j + 1], b); }
    return fold_add(a, b);
  }
  uint32_t q0[2], q1[2];
#pragma unroll
  for (int j = 0; j < 12; j++) {
    const uint32_t u = z[2 * j], v = z[2 * j + 1];
    q0[j & 1] = j < 2 ? h2mul(u, u) : h2fma(u, u, q0[j & 1]); q1[j & 1] = j < 2 ? h2mul(v, v) : h2fma(v, v, q1[j & 1]);
  }
  return fold_add(h2add(q0[0], q0[1]), h2add(q1[0], q1[1]));
}
__device__ __forceinline__ uint32_t rowsum(const uint32_t* z) {
  uint32_t a[2], b[2];
#pragma unroll
  for (int r = 0; r < 2; r++) {
    a[r] = h2add(h2add(h2add(z[r], z[r + 2]), h2add(z[r + 4], z[r + 6])), h2add(z[r + 8], z[r + 10]));
    b[r] = h2add(h2add(h2add(z[r + 12], z[r + 14]), h2add(z[r + 16], z[r + 18])), h2add(z[r + 20], z[r + 22]));
  }
  return fold_add(h2add(a[0], b[0]), h2add(a[1], b[1]));
}
__device__ __forceinline__ void scores_e(uint32_t* e, const uint32_t* q, const uint32_t* z) {
  uint32_t d[4];
#pragma unroll
  for (int j = 0; j < 12; j++) {
#pragma unroll
    for (int k = 0; k < 4; k++) d[k] = j ? h2fma(q[2 * j + (k >> 1)], z[2 * j + (k & 1)], d[k]) : h2mul(q[k >> 1], z[k & 1]);
  }
  e[0] = fold_add(d[0], d[2]); e[1] = fold_add(d[1], d[3]);
}
__device__ __forceinline__ uint32_t scores_r(const uint32_t* e, uint32_t selK) {
  return h2add(prmt(e[0], e[1], selK), __shfl_xor_sync(0xffffffffu, prmt(e[0], e[1], selK ^ 0x2222u), 1));
}
__device__ __forceinline__ uint32_t scores(const uint32_t* q, const uint32_t* z, uint32_t selK) {
  uint32_t e[2];
  scores_e(e, q, z);
  return scores_r(e, selK);
}
__device__ __forceinline__ float2 rstd(float2 d) { return make_float2(rsq_fast(fmaf(d.x, 1.f / 96.f, 1e-5f)), rsq_fast(fmaf(d.y, 1.f / 96.f, 1e-5f))); }
__device__ __forceinline__ void ln1_f32(uint32_t* z, const A3& la, int t, float* ie, float* m) {
  float acc[48];
  uint32_t x0[12], x1[12];
  load_row(x0, la, t); load_row(x1, la, t + 1);
#pragma unroll
  for (int j = 0; j < 12; j++) {
    acc[4 * j] = __uint_as_float(x0[j] << 16); acc[4 * j + 1] = __uint_as_float(x0[j] & 0xffff0000u);
    acc[4 * j + 2] = __uint_as_float(x1[j] << 16); acc[4 * j + 3] = __uint_as_float(x1[j] & 0xffff0000u);
  }
  float s[4], q[4];
#pragma unroll
  for (int e = 0; e < 4; e++) { s[e] = acc[e]; q[e] = acc[e] * acc[e]; }
#pragma unroll
  for (int j = 4; j < 48; j++) { s[j & 3] += acc[j]; q[j & 3] = fmaf(acc[j], acc[j], q[j & 3]); }
  const float s0 = quad_sum(s[0] + s[1]), s1 = quad_sum(s[2] + s[3]), q0 = quad_sum(q[0] + q[1]), q1 = quad_sum(q[2] + q[3]);
  const float u0 = rsq_fast(fmaxf(fmaf(-s0, s0, fmaf(q0, 96.f, kEps96)), kEps96));
  const float u1 = rsq_fast(fmaxf(fmaf(-s1, s1, fmaf(q1, 96.f, kEps96)), kEps96));
  const float n0 = -s0 * u0, n1 = -s1 * u1;
  ie[0] = 96.f * u0; ie[1] = 96.f * u1;
  m[0] = s0 * (1.f / 96.f); m[1] = s1 * (1.f / 96.f);
#pragma unroll
  for (int j = 0; j < 12; j++) {
    const int e = 4 * (j & ~1) + (j & 1);
    z[2 * j] = pack_h2(fmaf(acc[e], ie[0], n0), fmaf(acc[e + 4], ie[0], n0));
    z[2 * j + 1] = pack_h2(fmaf(acc[e + 2], ie[1], n1), fmaf(acc[e + 6], ie[1], n1));
  }
}
__device__ __forceinline__ float2 sumsq_f32(const uint32_t* z) {
  float2 qq = make_float2(0.f, 0.f);
#pragma unroll
  for (int j = 0; j < 12; j++) {
    const float2 u = unpack_h2(z[2 * j]), v = unpack_h2(z[2 * j + 1]);
    qq.x = fmaf(u.x, u.x, fmaf(u.y, u.y, qq.x)); qq.y = fmaf(v.x, v.x, fmaf(v.y, v.y, qq.y));
  }
  return make_float2(quad_sum(qq.x), quad_sum(qq.y));
}
__device__ __forceinline__ float2 var96_f32(const uint32_t* z, uint32_t my) {
  const float2 q = sumsq_f32(z), m = unpack_h2(my);
  return make_float2(fmaf(-96.f * m.x, m.x, q.x), fmaf(-96.f * m.y, m.y, q.y));
}
__device__ __forceinline__ void ln2(uint32_t* h, uint32_t rr, uint32_t my, const A3& ma, int t) {
  const uint32_t nn = as_u(__hmul2(__hneg2(as_h2(my)), as_h2(rr)));
#pragma unroll
  for (int j = 0; j < 12; j++) { h[2 * j] = h2fma(h[2 * j], lo2(rr), lo2(nn)); h[2 * j + 1] = h2fma(h[2 * j + 1], hi2(rr), hi2(nn)); }
#pragma unroll
  for (int k = 0; k < 3; k++) { stsm4(ma.a[k] + t * kFrame, h + 8 * k); stsm4((ma.a[k] ^ 32) + t * kFrame, h + 8 * k + 4); }
}

__device__ __forceinline__ uint32_t ring_pos(uint32_t r) { return min(r, r - 196u); }
__device__ __forceinline__ uint32_t ring_row(uint32_t r) { return ((r * 1338u) >> 16) * (kBufStride - kChunk) + r * 64; }
__device__ __forceinline__ uint32_t ring_stat(uint32_t r) { return ((r * 1338u) >> 16) * (kBufStride - 49 * 4) + r * 4; }
__device__ __forceinline__ A3 t_in_addr(uint32_t sb, uint32_t r0, int lane) {
  return swz3(sb + kOffBuf + (lane & 3) * 16 + ring_row(ring_pos(r0 + (lane >> 2))));
}
__device__ __forceinline__ A3 t_out_addr(uint32_t sb, uint32_t r0, int lane) {
  return swz3(sb + kOffBuf + ((lane >> 3) & 1) * kFrame + (lane & 16) + ring_row(ring_pos(r0 + (lane & 7))));
}
__device__ __forceinline__ uint32_t t_stat_addr(uint32_t sb, uint32_t r0, int lane) {
  return sb + kOffBuf + kXBytes + (lane & 3) * kFrame + ring_stat(ring_pos(r0 + (lane >> 2)));
}
__device__ __forceinline__ void t_release(uint32_t bar, uint32_t ia, uint32_t ib, int lane) {
  __syncwarp();
  asm volatile("{\n.reg .pred p;\nsetp.le.u32 p, %1, %2;\n@p mbarrier.arrive.shared::cta.b64 _, [%0];\n}"
               ::"r"(bar + ((ia + lane) & 3) * 8), "r"(lane), "r"(ib - ia) : "memory");
}
template <bool kDirect>
__device__ __forceinline__ void softmax4(uint32_t* s, uint32_t rhoA, uint32_t rhoB, uint32_t ro, float f) {
  if (kDirect) { s[0] = h2mul(s[0], rhoA); s[1] = h2mul(s[1], rhoB); }
  uint32_t mx = h2max(s[0], s[1]);
  mx = h2max(lo2(mx), hi2(mx));
  if (kDirect) {
    const uint32_t nm = as_u(__hmul2(__hneg2(as_h2(mx)), as_h2(ro)));
    s[0] = h2fma(s[0], ro, nm); s[1] = h2fma(s[1], ro, nm);
  } else {
    s[0] = h2mul(h2sub(s[0], mx), ro); s[1] = h2mul(h2sub(s[1], mx), ro);
  }
  s[0] = h2ex2(s[0]); s[1] = h2ex2(s[1]);
  uint32_t sm = h2add(s[0], s[1]);
  sm = h2add(lo2(sm), hi2(sm));
  const float iv = f * rcp_fast(__low2float(as_h2(sm)));
  const uint32_t inv = pack_h2(iv, iv);
  if (kDirect) { s[0] = h2mul(h2mul(s[0], rhoA), inv); s[1] = h2mul(h2mul(s[1], rhoB), inv); }
  else { s[0] = h2mul(s[0], inv); s[1] = h2mul(s[1], inv); }
}
template <bool kFirst>
__device__ __forceinline__ void mix(uint32_t* u, const uint32_t* z, uint32_t p0, uint32_t p1) {
  if ((AB & 32) && !kFirst) { u[0] = h2fma(z[0], p0, u[0]); u[1] = h2fma(z[1], p1, u[1]); return; }
#pragma unroll
  for (int j = 0; j < 12; j++) {
    u[2 * j] = h2fma(z[2 * j + 1], hi2(p0), kFirst ? h2mul(z[2 * j], lo2(p0)) : h2fma(z[2 * j], lo2(p0), u[2 * j]));
    u[2 * j + 1] = h2fma(z[2 * j + 1], hi2(p1), kFirst ? h2mul(z[2 * j], lo2(p1)) : h2fma(z[2 * j], lo2(p1), u[2 * j + 1]));
  }
}
template <bool kDirect>
__device__ __forceinline__ void put_stats(uint32_t sa, float sg, float mm, const Params& P) {
  const bool ok = (sg >= P.sgmin) & (kDirect || fmaf(sg, 9.8f, fabsf(mm)) < fmaf(P.kappa, -627.2f, 60000.f));
  const uint32_t sh = pack_h2(sg, mm), sw = pack_bf2(-sg, mm);
  asm volatile("st.shared.b32 [%0], %1;" ::"r"(sa), "r"(ok ? sh : sw) : "memory");
}

__device__ __forceinline__ bool task_T(uint32_t sb, uint32_t r0, uint32_t ia, uint32_t ib, uint32_t flag, int lane, const Params& P TRARG) {
  TR(1);
  const int c = lane & 3;
  const uint32_t selK = (c & 1) ? 0x7632u : 0x5410u, selO = 0x1010u + c * 0x2222u;
  const uint64_t da = mk_desc(sb, 1), dw = mk_desc(sb + kOffWt, 1);
  uint32_t x[48], yA[24], yB[24], qA[26], qB[26], ssA, ssB;
  {
    const A3 la = t_in_addr(sb, r0, lane);
#pragma unroll
    for (int e = 0; e < 12; e++) {
      const int t = 2 * (e / 6) + (e & 1), k = (e % 6) >> 1, ep = e - SM, tp = 2 * (ep / 6) + (ep & 1), kp = (ep % 6) >> 1;
      if (ep >= 0) hold(sb, x[12 * tp + 4 * kp]);
      lds128(x + 12 * t + 4 * k, la.a[k] + t * kFrame);
    }
  }
  row_to_h2(yA, x); row_to_h2(yA + 1, x + 12);
  x_work<7>(sb, x[5]);
  TR(2);
  row_to_h2(yB, x + 24); row_to_h2(yB + 1, x + 36);
  ssB = sumsq<C1>(yB);
  ssA = sumsq<C1>(yA);
  if (SPL & 1) gemm_at2(qA, yA, da); else gemm_at(qA, yA, da);
  if (SPL & 2) gemm_at2(qB, yB, da); else gemm_at(qB, yB, da);
  TR(3);
  ssB = quad_h2add(ssB);
  ssA = quad_h2add(ssA);
  uint32_t rA[2], rB[2];
  wg_wait<1>(); pin<26>(qA);
  x_work<11>(sb, qA[5]);
  TR(4);
  const uint32_t myA = __byte_perm(qA[24], qA[25], 0x5410), nuA = __byte_perm(qA[24], qA[25], 0x7632);
  const uint32_t nsA = h2mul(myA, 0xd600d600u);
  const float2 ra = rstd(unpack_h2(h2fma(nsA, myA, ssA)));
  const uint32_t rhoA = pack_h2(ra.x, ra.y);
  rA[0] = scores(qA, yA, selK);
  if (HD & 2) { hold(sb, rA[0]); hold(sb, rhoA); } else sched_fence(rA[0], rhoA, 0);
  wg_wait<0>(); pin<26>(qB);
  TR(5);
  const uint32_t myB = __byte_perm(qB[24], qB[25], 0x5410), nuB = __byte_perm(qB[24], qB[25], 0x7632);
  const uint32_t nsB = h2mul(myB, 0xd600d600u);
  const float2 rb = rstd(unpack_h2(h2fma(nsB, myB, ssB)));
  const uint32_t rhoB = pack_h2(rb.x, rb.y);
  const uint32_t ro = prmt(rhoA, rhoB, selO), mo = bitsel(prmt(myA, myB, selO), 0xffffu, 0x292e0000u);
  asm volatile("{\n.reg .pred p, q;\n.reg .b32 t;\nabs.f16x2 t, %1;\nsetp.gtu.f16x2 p|q, t, %2;\nor.pred p, p, q;\n@p st.volatile.shared.b32 [%0], %2;\n}"
               ::"r"(flag), "r"(h2fma(ro, mo, 0xbc190000u)), "r"(0x3c003c00u) : "memory");
  uint32_t mu;
  rA[1] = scores(qA, yB, selK); rB[0] = scores(qB, yA, selK); rB[1] = scores(qB, yB, selK);
  uint32_t p[8], s[2];
#pragma unroll
  for (int k = 0; k < 2; k++) s[k] = h2add((c & 2) ? rB[k] : rA[k], __shfl_xor_sync(0xffffffffu, (c & 2) ? rA[k] : rB[k], 2));
  softmax4<true>(s, rhoA, rhoB, ro, P.kt);
#pragma unroll
  for (int t = 0; t < 4; t++) { p[2 * t] = __shfl_sync(0xffffffffu, s[0], t, 4); p[2 * t + 1] = __shfl_sync(0xffffffffu, s[1], t, 4); }
  mu = h2fma(s[1], nuB, h2mul(s[0], nuA));
  mix<true>(qA, yA, p[0], p[2]); mix<false>(qA, yB, p[1], p[3]);
  mu = h2add(lo2(mu), hi2(mu));
  mix<true>(qB, yA, p[4], p[6]);
  x_work<8>(sb, p[4]);
  TR(6);
  if (SPL & 4) gemm_w2(yA, qA, dw); else gemm_w<1>(yA, qA, dw);
  sched_fence(0, 0, 0);
  mix<false>(qB, yB, p[5], p[7]);
  if (SPL & 8) gemm_w2(yB, qB, dw); else gemm_w<1>(yB, qB, dw);
  const A3 ma = t_out_addr(sb, r0, lane);
  if (HD & 4) hold(sb, ma.a[0] ^ ma.a[1] ^ ma.a[2]);
  x_work<9>(sb, mu);
  TR(7);
  wg_wait<1>(); pin<24>(yA);
  TR(8);
  uint32_t bad;
  asm volatile("ld.shared.b32 %0, [%1];" : "=r"(bad) : "r"(flag + (yA[0] & (gridDim.x == 0x7fffffffu))) : "memory");
  float2 d = unpack_h2(h2fma(nsA, myA, quad_h2add(sumsq<C2>(yA))));
  if (UNLIKELY(__any_sync(0xffffffffu, !(d.x + d.y < 65000.f) | (bad != 0)))) {
    if (__any_sync(0xffffffffu, bad != 0)) {
      wg_wait<0>(); pin<24>(yB);
      return false;
    }
    d = var96_f32(yA, myA);
  }
  float2 r = rstd(make_float2(fabsf(d.x), fabsf(d.y)));
  const uint32_t rrA = pack_h2(r.x, r.y);
  ln2(yA, rrA, myA, ma, 0);
  if (DA) t_release(sb + kOffBar + 32, ia, ib, lane);
  wg_wait<0>(); pin<24>(yB);
  x_work<10>(sb, yB[5]);
  TR(9);
  d = unpack_h2(h2fma(nsB, myB, quad_h2add(sumsq<C2>(yB))));
  if (UNLIKELY(__any_sync(0xffffffffu, !(d.x + d.y < 65000.f)))) d = var96_f32(yB, myB);
  r = rstd(make_float2(fabsf(d.x), fabsf(d.y)));
  const uint32_t rrB = pack_h2(r.x, r.y);
  ln2(yB, rrB, myB, ma, 2);
  put_stats<true>(t_stat_addr(sb, r0, lane), rcp_fast(__low2float(as_h2(prmt(rrA, rrB, selO)))), __low2float(as_h2(CM ? prmt(myA, myB, selO) : h2add(mo, mu))), P);
  return true;
}

__device__ __forceinline__ void task_T_general(uint32_t sb, uint32_t r0, const Params& P) {
  int lane;
  asm volatile("mov.u32 %0, %%laneid;" : "=r"(lane));
  const int c = lane & 3;
  const uint64_t da = mk_desc(sb, 1), dw = mk_desc(sb + kOffWt, 1);
  uint32_t yA[24], yB[24], qA[26], qB[26];
  float ieo, mo, ao;
  {
    float ie[4], m[4];
    const A3 la = t_in_addr(sb, r0, lane);
    ln1_f32(yA, la, 0, ie, m);
    ln1_f32(yB, la, 2, ie + 2, m + 2);
    const float2 na = sumsq_f32(yA), nb = sumsq_f32(yB);
    const float ik = 9.8f * rcp_fast(P.kt) * rsq_fast(fmaxf(fmaxf(fmaxf(na.x, na.y), fmaxf(nb.x, nb.y)), 2e-7f));
    ieo = (c & 2) ? ((c & 1) ? ie[3] : ie[2]) : ((c & 1) ? ie[1] : ie[0]);
    mo = (c & 2) ? ((c & 1) ? m[3] : m[2]) : ((c & 1) ? m[1] : m[0]);
    const bool lim = (ieo * P.kt > 400.f) & (ik < ieo);
    const float u = ik * rcp_fast(ieo);
    ao = lim ? u : 1.f; ieo = lim ? ik : ieo;
  }
  uint32_t rA[2], rB[2], s[2], p[8];
  const uint32_t selK = (c & 1) ? 0x7632u : 0x5410u;
  gemm_at(qA, yA, da);
  wg_wait<0>(); pin<26>(qA);
  const uint32_t nuA = __byte_perm(qA[24], qA[25], 0x7632);
  rA[0] = scores(qA, yA, selK); rA[1] = scores(qA, yB, selK);
  sched_fence(rA[0], rA[1], nuA);
  gemm_at(qB, yB, da);
  wg_wait<0>(); pin<26>(qB);
  const uint32_t nuB = __byte_perm(qB[24], qB[25], 0x7632);
  rB[0] = scores(qB, yA, selK); rB[1] = scores(qB, yB, selK);
#pragma unroll
  for (int k = 0; k < 2; k++) s[k] = h2add((c & 2) ? rB[k] : rA[k], __shfl_xor_sync(0xffffffffu, (c & 2) ? rA[k] : rB[k], 2));
  softmax4<false>(s, 0, 0, score_scale(&g_par.cS_t), P.kt * ieo);
  uint32_t mu = h2fma(s[1], nuB, h2mul(s[0], nuA));
  mu = h2add(lo2(mu), hi2(mu));
#pragma unroll
  for (int t = 0; t < 4; t++) { p[2 * t] = __shfl_sync(0xffffffffu, s[0], t, 4); p[2 * t + 1] = __shfl_sync(0xffffffffu, s[1], t, 4); }
  sched_fence(mu, 0, 0);
  mix<true>(qA, yA, p[0], p[2]); mix<false>(qA, yB, p[1], p[3]);
  mix<true>(qB, yA, p[4], p[6]); mix<false>(qB, yB, p[5], p[7]);
  const uint32_t ah = pack_h2(ao, ao);
#pragma unroll
  for (int t = 0; t < 4; t++) {
    const uint32_t a = __shfl_sync(0xffffffffu, ah, t, 4);
#pragma unroll
    for (int j = 0; j < 12; j++) asm volatile("mul.f16x2 %0, %0, %1;" : "+r"(((t & 2) ? yB : yA)[2 * j + (t & 1)]) : "r"(a));
  }
  gemm_w<1>(yA, qA, dw);
  gemm_w<1>(yB, qB, dw);
  wg_wait<0>(); pin<24>(yA); pin<24>(yB);
  asm volatile("mov.u32 %0, %%laneid;" : "=r"(lane));
  float ie[4];
#pragma unroll
  for (int t = 0; t < 4; t++) ie[t] = __shfl_sync(0xffffffffu, ieo, t, 4);
  const float2 da2 = sumsq_f32(yA), db2 = sumsq_f32(yB);
  const uint32_t rrA = pack_h2_sat(rsq_fast(fmaf(da2.x, 1.f / 96.f, 1e-5f * ie[0] * ie[0])), rsq_fast(fmaf(da2.y, 1.f / 96.f, 1e-5f * ie[1] * ie[1])));
  const uint32_t rrB = pack_h2_sat(rsq_fast(fmaf(db2.x, 1.f / 96.f, 1e-5f * ie[2] * ie[2])), rsq_fast(fmaf(db2.y, 1.f / 96.f, 1e-5f * ie[3] * ie[3])));
  const A3 ma = t_out_addr(sb, r0, lane);
  ln2(yA, rrA, 0u, ma, 0); ln2(yB, rrB, 0u, ma, 2);
  const float r = __low2float(as_h2(prmt(rrA, rrB, 0x1010u + (lane & 3) * 0x2222u))), sg = rcp_fast(r * ieo);
  put_stats<false>(t_stat_addr(sb, r0, lane), sg, fmaf(__low2float(as_h2(mu)) * r, sg, mo), P);
}

__device__ __forceinline__ void claim(uint32_t sb, uint32_t nfull) {
  const uint32_t nb = gridDim.x, nrem = kNWIN - nfull * nb;
  const uint32_t whole = max((int)(nrem * NWH / 49), (int)(2 * nrem - nb));
  uint32_t t = blockIdx.x;
  if (DYN) asm volatile("atom.relaxed.gpu.global.inc.u32 %0, [%1], 0x7fffffff;" : "=r"(t) : "l"(&g_ctr) : "memory");
  const uint32_t u = t - whole;
  sts32(sb + kOffClaim, t < whole ? (nfull * nb + t) | 0x10000u
                        : u < 2 * (nrem - whole) ? (nfull * nb + whole + (u >> 1)) | 0x50000u | ((u & 1) << 17)
                        : blockIdx.x + (nfull - 1) * nb);
}
__device__ __forceinline__ void loop_T(uint32_t sb, int nfull, int wg, int wp, int lane, const Params& P, bool direct TRARG) {
  const uint32_t barF = sb + kOffBar, barD = sb + (DA ? kOffBarB : kOffBar + 32), flag = sb + kOffFlag + wg * 4;
  mbar_wait(sb + kOffBarW, 0);
  uint32_t r0 = 32 * wg + 8 * wp, par = 0;
  int k = (49 * nfull + 63 - 32 * wg) >> 6;
  int kx = ((49 * nfull + 112 - 32 * wg) >> 6) - k;
  int kc = wg + wp ? 0 : k - ((49 * (nfull - 3) - 1) >> 6);
  for (;;) {
    TR(0);
    if (UNLIKELY(k <= kc)) {
      if (k) {
        if (lane == 0) claim(sb, nfull);
        __syncwarp();
        kc = 0;
      } else {
        mbar_wait(barF + (nfull & 3) * 8, (nfull >> 2) & 1);
        k = __any_sync(0xffffffffu, lds32(sb + kOffClaim) & 0x10000u) ? kx : 0;
        kx = 0;
        if (k == 0) break;
      }
    }
    k--;
    const uint32_t ia = (r0 * 1338u) >> 16, ib = ((r0 + 7) * 1338u) >> 16;
    mbar_wait(barF + ia * 8, par);
    if (UNLIKELY(ib != ia)) mbar_wait(barF + (ib & 3) * 8, par ^ (ib >> 2));
    const uint32_t r = r0;
    r0 += 64;
    if (r0 >= 196) { r0 -= 196; par ^= 1; }
    if (LIKELY(direct)) {
      if (LIKELY(task_T(sb, r, ia, ib, flag, lane, P TRPASS(trp)))) {
        t_release(barD, ia, ib, lane);
        continue;
      }
      asm volatile("barrier.cta.sync.aligned %0, 128;" ::"r"(wg + 1) : "memory");
      asm volatile("st.shared.b32 [%0], %1;\nfence.acq_rel.cta;" ::"r"(flag), "r"(0) : "memory");
    }
    task_T_general(sb, r, P);
    if (DA) t_release(sb + kOffBar + 32, ia, ib, lane);
    t_release(barD, ia, ib, lane);
  }
}

struct SFrame {
  uint32_t oo;
  uint32_t t;
  uint32_t st;
  uint32_t d;
  bool light;
};
__device__ __forceinline__ SFrame s_frame(uint32_t sb, int t, int wp, int lane, A3& ma) {
  SFrame f;
  const int rb = (wp + t) & 3;
  f.light = rb == 3;
  f.t = t;
  f.d = ((sb + kOffBuf + t * kFrame) >> 4) & 0x3fff;
  f.st = t * kFrame + kXBytes + rb * 64;
  ma = swz3(t * kFrame + rb * 1024 + ((lane * 65) & 0x3d0));
  if (f.light && (lane & 15)) ma.a[0] = ma.a[1] = ma.a[2] = kXBytes + 256;
  const uint32_t r = 16 * rb + (lane >> 2);
  f.oo = (r + (r / 7) * (kW - 7)) * 12 + (lane & 3) + (((r + 8 + ((r + 8) / 7) * (kW - 7)) * 12 + (lane & 3)) << 16);
  asm volatile("" : "+r"(f.oo));
  return f;
}
template <int kRow>
__device__ __forceinline__ uint8_t* out_row(uint8_t* ob, const SFrame& f) {
  uint32_t o = f.oo;
  asm volatile("" : "+r"(o));
  uint8_t* r;
  asm("mad.wide.u32 %0, %1, 16, %2;" : "=l"(r) : "r"(kRow ? o >> 16 : o & 0xffffu), "l"(ob));
  return r;
}
template <int kHi, int kFrom = 0, int kTo = 6>
__device__ __forceinline__ void s_load(uint32_t (&v)[24], uint32_t buf, A3 ma) {
  asm volatile("" : "+r"(ma.a[0]), "+r"(ma.a[1]), "+r"(ma.a[2]));
#pragma unroll
  for (int e = kFrom; e < kTo; e++) {
    const uint32_t a = kHi ? ma.a[e >> 1] >> 16 : ma.a[e >> 1] & 0xffffu;
    if (AB & 8) ldsm4x(v + 4 * e, buf + ((e & 1) ? a ^ 32 : a)); else ldsm4(v + 4 * e, buf + ((e & 1) ? a ^ 32 : a));
  }
}
__device__ __forceinline__ void gemm_s(uint32_t* s, const uint32_t* q, uint64_t dA) {
  wg_fence();
  wg56h<0>(s, q, dA); wg56h<1>(s, q + 4, dA + 2);
  wg56h<1>(s, q + 8, dA + 196); wg56h<1>(s, q + 12, dA + 198);
  wg56h<1>(s, q + 16, dA + 392); wg56h<1>(s, q + 20, dA + 394);
  wg_commit();
}
template <bool kAll>
__device__ __forceinline__ void stg128(uint8_t* o, const uint32_t* w, uint32_t doit) {
  if (kAll) asm volatile("st.global.v4.b32 [%0], {%1,%2,%3,%4};" ::"l"(o), "r"(w[0]), "r"(w[1]), "r"(w[2]), "r"(w[3]) : "memory");
  else asm volatile("{\n.reg .pred p;\nsetp.ne.u32 p, %5, 0x7bff;\n@p st.global.v4.b32 [%0], {%1,%2,%3,%4};\n}" ::"l"(o), "r"(w[0]), "r"(w[1]), "r"(w[2]), "r"(w[3]), "r"(doit) : "memory");
}
template <int kRow, bool kAll>
__device__ __forceinline__ void s_store(const uint32_t (&v)[24], uint32_t e, uint8_t* o) {
  uint32_t w[12];
#pragma unroll
  for (int j = 0; j < 12; j += 2) {
    const float2 y = unpack_h2(h2fma(v[2 * j + kRow], lo2(e), hi2(e))), z = unpack_h2(h2fma(v[2 * j + 2 + kRow], lo2(e), hi2(e)));
    w[j] = pack_bf2(y.x, z.x); w[j + 1] = pack_bf2(y.y, z.y);
  }
#pragma unroll
  for (int i3 = 0; i3 < 3; i3++) stg128<kAll>(o + 64 * i3, w + 4 * i3, e);
}
template <int kRow, bool kAdd>
__device__ __forceinline__ void s_store_wide(const uint32_t (&v)[24], uint32_t e, uint8_t* o, const Params& P) {
  const float2 z = stat_f32(e);
#pragma unroll
  for (int i3 = 0; i3 < 3; i3++) {
    uint32_t w[4] = {0, 0, 0, 0};
    if (kAdd)
      asm volatile("{\n.reg .pred p;\nsetp.ne.u32 p, %5, 0x7bff;\n@p ld.global.v4.b32 {%0,%1,%2,%3}, [%4];\n}"
                   : "+r"(w[0]), "+r"(w[1]), "+r"(w[2]), "+r"(w[3]) : "l"(o + 64 * i3), "r"(e) : "memory");
#pragma unroll
    for (int j = 0; j < 4; j++) {
      const float2 ya = unpack_h2(v[8 * i3 + 2 * (j & 2) + kRow]), yb = unpack_h2(v[8 * i3 + 2 * (j & 2) + 2 + kRow]);
      const float2 y = (j & 1) ? make_float2(ya.y, yb.y) : make_float2(ya.x, yb.x);
      w[j] = kAdd ? pack_bf2(fmaf(y.x, P.kappa, __uint_as_float(w[j] << 16)), fmaf(y.y, P.kappa, __uint_as_float(w[j] & 0xffff0000u)))
                  : pack_bf2(fmaf(y.x, z.x, z.y), fmaf(y.y, z.x, z.y));
    }
    stg128<false>(o + 64 * i3, w, e);
  }
  __syncwarp();
}
__device__ __forceinline__ uint32_t ex2_pair(uint32_t s, uint32_t sel) {
  if (AB & 64) return (s & 0x03ff03ffu) | 0x3c003c00u;
  uint32_t lo, hi;
  asm volatile("{\n.reg .b16 a, b, c;\nmov.b32 {a, b}, %2;\nex2.approx.f16 c, a;\ncvt.u32.u16 %0, c;\nex2.approx.f16 c, b;\ncvt.u32.u16 %1, c;\n}"
               : "=r"(lo), "=r"(hi) : "r"(s));
  return QP ? prmt(lo, hi, sel) : lo + hi * 65536u;
}
__device__ __forceinline__ uint32_t ex2_lo(uint32_t s) {
  uint32_t lo;
  asm volatile("{\n.reg .b16 a, b, c;\nmov.b32 {a, b}, %1;\nex2.approx.f16 c, a;\ncvt.u32.u16 %0, c;\n}" : "=r"(lo) : "r"(s));
  return lo;
}

__device__ __forceinline__ void turn_wait(uint32_t j) { asm volatile("barrier.cta.sync.aligned %0, 256;" ::"r"(5 + j) : "memory"); }
__device__ __forceinline__ void turn_pass(uint32_t j) { asm volatile("barrier.cta.arrive.aligned %0, 256;" ::"r"(6 - j) : "memory"); }

template <int kSecond>
__device__ __forceinline__ void step_S(uint32_t sb, uint32_t (&v)[24], uint32_t (&vn)[24], uint32_t (&q)[24], uint32_t (&s)[16], const SFrame& f,
                                       const SFrame& fn, const A3& ma, uint32_t i, uint32_t nfull, uint32_t w4, uint32_t& cl, uint8_t* ob, int lane, const Params& P,
                                       bool scaled, const CUtensorMap* tm TRARG) {
  TR(0);
  const uint32_t ia = i & 3, ib = kSecond ? (i + 1) & 3 : ia;
  const uint32_t buf = sb + kOffBuf + ia * kBufStride, bufn = sb + kOffBuf + ib * kBufStride;
  const uint32_t never = gridDim.x == 0x7fffffffu;
  const uint64_t dQ0 = mk_desc(sb + kOffAs, 1), dQ = (HQ & 1) ? dQ0 : dQ0 + ((i + kSecond) & never), dW = ((HQ & 2) ? dQ0 : dQ0 + ((i + kSecond) & never)) + (kWMat >> 4);
  uint32_t p[16], u[24], e0, e1;
  ob += f.t * (kH * kW * 192u);
  const uint32_t nw = nfull + ((cl >> 16) & 1);
  asm volatile("" : "+l"(ob));
  const uint32_t sta = buf + f.st + (lane & 0x1c);
  asm volatile("ld.shared.b32 %0, [%1];" : "=r"(e0) : "r"(sta) : "memory");
  asm volatile("ld.shared.b32 %0, [%1];" : "=r"(e1) : "r"(sta + 32) : "memory");
  constexpr int kLP = kSecond ? LP1 : LP0;
  auto loadp = [&](int pos) {
    if (pos != kLP) return;
    if (kSecond && i + 1 < nw) mbar_wait(sb + kOffBar + 32 + ib * 8, ((i + 1) >> 2) & 1);
    s_load<!kSecond, 0, LA>(vn, bufn, ma);
  };
  loadp(2);
  const uint32_t keep = (lane & 3) == 0 ? 0x0000ffffu : 0u;
  const bool pad0 = QP && f.light && lane >= 4, pad1 = QP && f.light;
  const uint32_t sel0 = pad0 ? 0x3232u : 0x5410u, sel1 = pad1 ? 0x3232u : 0x5410u;
  s[12] = bitsel(s[12], QP == 1 && pad0 ? 0u : keep, 0xfc00fc00u); s[13] = bitsel(s[13], QP == 1 && pad1 ? 0u : keep, 0xfc00fc00u);
  const uint32_t x0 = h2max(h2max(h2max(h2max(s[0], s[2]), s[4]), h2max(h2max(s[6], s[8]), s[10])), s[12]);
  const uint32_t x1 = h2max(h2max(h2max(h2max(s[1], s[3]), s[5]), h2max(h2max(s[7], s[9]), s[11])), s[13]);
  uint32_t okv;
  asm("{\n.reg .pred p, q;\nsetp.le.f16x2 p|q, %1, %2;\nand.pred p, p, q;\nselp.u32 %0, 1, 0, p;\n}"
      : "=r"(okv) : "r"(as_u(__hmax2(__habs2(as_h2(x0)), __habs2(as_h2(x1))))), "r"(0x47004700u));
  const bool ok = (okv != 0) & !scaled;
  constexpr int kE = IL == 0 ? 12 : IL == 1 ? 4 : IL == 2 ? 0 : 8;
  p[12] = ex2_lo(s[12]); p[13] = ex2_lo(s[13]);
  if (QP == 3) { p[12] = prmt(p[12], 0, sel0); p[13] = prmt(p[13], 0, sel1); }
#pragma unroll
  for (int j = 0; j < kE; j++) p[j] = ex2_pair(s[j], (j & 1) ? sel1 : sel0);
  if (UNLIKELY(!__all_sync(0xffffffffu, ok))) {
    uint32_t mx = h2max(__byte_perm(x0, x1, 0x5410), __byte_perm(x0, x1, 0x7632));
    mx = h2max(mx, __shfl_xor_sync(0xffffffffu, mx, 1));
    mx = h2max(mx, __shfl_xor_sync(0xffffffffu, mx, 2));
    const uint32_t cs = lds32(sb + kOffCs);
#pragma unroll
    for (int j = 0; j < 7; j++) { s[2 * j] = h2mul(h2sub(s[2 * j], lo2(mx)), cs); s[2 * j + 1] = h2mul(h2sub(s[2 * j + 1], hi2(mx)), cs); }
    p[12] = ex2_lo(s[12]); p[13] = ex2_lo(s[13]);
  if (QP == 3) { p[12] = prmt(p[12], 0, sel0); p[13] = prmt(p[13], 0, sel1); }
#pragma unroll
    for (int j = 0; j < kE; j++) p[j] = ex2_pair(s[j], (j & 1) ? sel1 : sel0);
  }
  asm volatile("mov.b32 %0, 0;\nmov.b32 %1, 0;" : "=r"(p[14]), "=r"(p[15]));
  x_work<1>(sb, s[5]);
  TR(1);
  const uint64_t mn = OB ? desc_at(f.d + ia * (kBufStride >> 4) + (kChunk >> 4 << 16)) : mk_desc(buf + f.t * kFrame, kChunk >> 4);
  wg_fence();
  wg96h<2, 1>(q, p + 12, mn + 192 - (SB0 ? 0x2000000000ull : 0ull), never); wg96h<1, 1>(q, p, mn);
  loadp(1);
#pragma unroll
  for (int j = 4; j < 12; j++) p[j] = ex2_pair(s[j], (j & 1) ? sel1 : sel0);
  loadp(4);
  uint32_t wf;
  asm("lop3.b32 %0, %1, %2, 0x8000, 0xa8;" : "=r"(wf) : "r"(e0), "r"(e1));
  const bool wide = __any_sync(0xffffffffu, (W1x ? wf : (e0 | e1) & 0x8000u) != 0u);
  uint32_t rs = R4x ? fold_add(h2add(h2add(h2add(h2add(h2add(p[0], p[2]), p[12]), h2add(p[4], p[6])), p[8]), p[10]),
                               h2add(h2add(h2add(h2add(h2add(p[1], p[3]), p[13]), h2add(p[5], p[7])), p[9]), p[11]))
                    : fold_add(h2add(h2add(h2add(p[0], p[2]), p[12]), h2add(h2add(p[4], p[6]), h2add(p[8], p[10]))),
                         h2add(h2add(h2add(p[1], p[3]), p[13]), h2add(h2add(p[5], p[7]), h2add(p[9], p[11])))), rt;
  asm volatile("shfl.sync.bfly.b32 %0, %1, 1, 31, 0xffffffff;" : "=r"(rt) : "r"(rs));
  uint32_t r2, r3;
  asm volatile("shfl.sync.bfly.b32 %0, %1, 2, 31, 0xffffffff;" : "=r"(r2) : "r"(rs));
  asm volatile("shfl.sync.bfly.b32 %0, %1, 3, 31, 0xffffffff;" : "=r"(r3) : "r"(rs));
  wg_fence();
  wg96h<1, 1>(q, p + 4, mn + 64); wg96h<1, 1>(q, p + 8, mn + 128);
  wg_commit();
  loadp(5);
  TR(2);
  float g0 = __low2float(as_h2(e0)), g1 = __low2float(as_h2(e1));
  if (UNLIKELY(wide)) {
    s_store_wide<0, false>(v, e0, out_row<0>(ob, f), P); s_store_wide<1, false>(v, e1, out_row<1>(ob, f), P);
    asm volatile("mov.b32 %0, %2;\nmov.b32 %1, %2;" : "=f"(g0), "=f"(g1) : "f"(P.kappa));
    if (R3) { rt += never; r2 += never; }
  }
  rs = h2add(rs, rt);
  rt = h2add(r2, r3);
  auto next = [&]() {
    if (i + 1 < nw) mbar_wait(sb + kOffBar + 32 + ib * 8, ((i + 1) >> 2) & 1);
    s_load<0>(vn, bufn, ma);
  };
  loadp(0);
  rs = h2add(rs, rt);
  const float d0 = __low2float(as_h2(rs)), d1 = __high2float(as_h2(rs));
  const float c0 = P.kappa * rcp_fast(d0 * g0), c1 = P.kappa * rcp_fast(d1 * g1);
  const uint32_t cb = OA == 3 ? pack_h2_sat(c0, c1) : OA == 2 ? pack_h2_rz(c0, c1) : OA ? pack_h2(c0, c1) : pack_h2(e0 != kPadStat ? c0 : 0.f, e1 != kPadStat ? c1 : 0.f);
  if (kLP == 7) hold(sb, cb);
  loadp(7);
  x_work<2>(sb, e0);
  if (HD & 1) hold(sb, cb);
  if (PG == 1) turn_wait(f.t & 1);
  wg_wait<0>(); pin<24>(q);
  s_load<!kSecond, LA, LB2>(vn, bufn, ma);
  x_work<3>(sb, q[5]);
  TR(3);
  if (PG == 2) turn_wait(f.t & 1);

  if (kSecond && LD == 2) next();
  auto refill = [&]() {
    if (EL) {
      if (f.light & (i + 4 <= nw)) {
        const uint32_t c = i + 4 >= nfull ? cl : w4;
        tma_load_elect<!kSecond>(buf + f.t * kFrame, tm, sb + kOffBar + ia * 8, c & 0xffffu, f.t ^ ((c >> 16) & 2), fn.t ^ ((c >> 16) & 2));
      }
    } else if (f.light) {
      const uint32_t bar = sb + kOffBar + ia * 8;
      if (lane == 0) {
        const uint32_t c = i + 4 >= nfull ? cl : w4;
        if (i + 4 <= nw) {
          tma_load(buf + f.t * kFrame, tm, bar, c & 0xffffu, f.t ^ ((c >> 16) & 2));
          if (!kSecond) tma_prefetch(tm, c & 0xffffu, fn.t ^ ((c >> 16) & 2));
        }
      }
      __syncwarp();
    }
  };
#pragma unroll
  for (int j = 0; j < 12; j++) { u[2 * j] = h2mul(q[2 * j], lo2(cb)); u[2 * j + 1] = h2mul(q[2 * j + 1], hi2(cb)); }
  if (PG == 3) turn_wait(f.t & 1);
  TR(4);
  gemm_w<2>(v, u, dW, !wide);
  if (PG && PR == 0) turn_pass(f.t & 1);
  if (LF && LB2 < 6) sched_fence(0, 0, 0);
  s_load<!kSecond, LB2, 6>(vn, bufn, ma);

  if (RF == 0 || ((RF == 1 || RF == 4) && kSecond)) refill();
  if (kSecond && LD == 0) next();
  gemm_w<2>(q, vn, dQ, never);
  if (RF == 2 || (RF == 1 && !kSecond)) refill();
  if (PG && PR == 1) turn_pass(f.t & 1);
  x_work<4>(sb, e0);
  TR(5);
  if (OH && kSecond && i + 1 < nw) mbar_wait(sb + kOffBarB + ib * 8, ((i + 1) >> 2) & 1);
  if (kSecond && UNLIKELY(i + 5 == nfull)) cl = __shfl_sync(0xffffffffu, lds32(sb + kOffClaim), 0);
  const bool plain = !(wide | f.light);
  wg_wait<1>(); pin<24>(v);
  if (kSecond || !OH) asm volatile("fence.proxy.async.shared::cta;" ::: "memory");
  if (PG && PR == 2) turn_pass(f.t & 1);
  x_work<5>(sb, v[5]);
  TR(6);
  if (LIKELY(plain)) s_store<0, true>(v, e0, out_row<0>(ob, f));
  else if (RF == 3 || (RF == 4 && !kSecond)) refill();
  if (PG && PR == 3) turn_pass(f.t & 1);
  wg_wait<0>(); pin<24>(q);
  TR(7);
  gemm_s(s, q, OB ? desc_at(fn.d + ib * (kBufStride >> 4) + (1 << 16)) : mk_desc(bufn + fn.t * kFrame, 1));
  if (PG && PR == 4) turn_pass(f.t & 1);

  if (LIKELY(plain)) s_store<1, true>(v, e1, out_row<1>(ob, f));
  else if (!wide) { s_store<0, false>(v, e0, out_row<0>(ob, f)); __syncwarp(); }
  else if (wide) { s_store_wide<0, true>(v, e0, out_row<0>(ob, f), P); s_store_wide<1, true>(v, e1, out_row<1>(ob, f), P); }
  if (kSecond && LP0 == 3) s_load<1>(v, bufn, ma);
  x_work<6>(sb, e0);
  if (PG && PR == 5) turn_pass(f.t & 1);
  if (!OH && kSecond && i + 1 < nw) mbar_wait(sb + kOffBarB + ib * 8, ((i + 1) >> 2) & 1);
  wg_wait<0>(); pin<14>(s);
}

__device__ __forceinline__ void loop_S(uint32_t sb, uint32_t nfull, int t0, int wp, int lane, const Params& P, bool scaled,
                                       const CUtensorMap* tm, uint8_t* __restrict__ out TRARG) {
  A3 ma, mb;
  const SFrame f0 = s_frame(sb, t0, wp, lane, ma), f1 = s_frame(sb, t0 + 2, wp, lane, mb);
#pragma unroll
  for (int k = 0; k < 3; k++) ma.a[k] += mb.a[k] << 16;
  uint32_t v0[24], v1[24], q[24], s[16];
  sts32(sb + kOffCs, pack_h2(P.cS_s, P.cS_s));
  mbar_wait(sb + kOffBarW + 8, 0);
  mbar_wait(sb + kOffBar + 32, 0);
  s_load<0>(v0, sb + kOffBuf, ma);
  gemm_w<0>(q, v0, mk_desc(sb + kOffAs, 1));
  if (OH) mbar_wait(sb + kOffBarB, 0);
  asm volatile("fence.proxy.async.shared::cta;" ::: "memory");
  wg_wait<0>(); pin<24>(q);
  gemm_s(s, q, mk_desc(sb + kOffBuf + f0.t * kFrame, 1));
  if (LP0 == 3) s_load<1>(v1, sb + kOffBuf, ma);
  wg_wait<0>(); pin<14>(s);
  if (PG && t0 == PF0) turn_pass(t0);
  uint32_t cl = 0, w0 = blockIdx.x;
  for (uint32_t i = 0;; i++, w0 += gridDim.x) {
    const bool more = i + 1 < nfull + ((cl >> 16) & 1);
    const uint32_t c = i == nfull ? cl : w0, w = c & 0xffffu;
    const uint32_t wy = (w * 57457u) >> 22;
    uint8_t* ob = out + (size_t)((wy * (7 * kW - 7 * kNWX) + w * 7 + ((c >> 16) & 2) * (kH * kW)) * 192u);
    asm volatile("" : "+l"(ob));
    step_S<0>(sb, v0, v1, q, s, f0, f1, ma, i, nfull, w0 + 4 * gridDim.x, cl, ob, lane, P, scaled, tm TRPASS(trp + 16 * i));
    if (c & 0x40000u) break;
    step_S<1>(sb, v1, v0, q, s, f1, f0, ma, i, nfull, w0 + 4 * gridDim.x, cl, ob, lane, P, scaled, tm TRPASS(trp + 16 * i + 8));
    if (!more) break;
  }
  if (PG && t0 != PF0) turn_wait(t0);
  const uint32_t nw = nfull + ((cl >> 16) & 1);
  mbar_wait(sb + kOffBar + (nw & 3) * 8, (nw >> 2) & 1);
}

__global__ void __launch_bounds__(LB, 1) swin_main(const __grid_constant__ Maps maps, uint8_t* __restrict__ out) {
  const CUtensorMap& tm = maps.tm;
  extern __shared__ __align__(1024) uint8_t smem[];
  const uint32_t sb = smem_u32(smem);
  const int tid = threadIdx.x;
  const int wg = __shfl_sync(0xffffffffu, tid >> 7, 0);
  const int wp = __shfl_sync(0xffffffffu, (tid >> 5) & 3, 0);
  const int lane = tid & 31;
  const int b = blockIdx.x, nb = gridDim.x;
  const int nfull = kNWIN / nb;
  if (tid == 0) {
    if ((sb & 1023) || nfull < 8) __trap();
#pragma unroll
    for (int i = 0; i < 4; i++) {
      mbar_init(sb + kOffBar + i * 8, 4);
      mbar_init(sb + kOffBar + 32 + i * 8, 7);
      mbar_init(sb + kOffBarB + i * 8, 7);
    }
    asm volatile("st.shared.v4.b32 [%0], {%1,%1,%1,%1};" ::"r"(sb + kOffFlag), "r"(0) : "memory");
    mbar_init(sb + kOffBarW, WP ? 8 : 1); mbar_init(sb + kOffBarW + 8, WP ? 8 : 1);
    asm volatile("fence.mbarrier_init.release.cluster;" ::: "memory");
  }
  if (tid >= 128 && tid < 488) {
    const uint32_t e = tid - 128, fr = min(e / 20, 15u);
    asm volatile("st.shared.v4.b32 [%0], {%1,%1,%1,%1};" ::"r"(sb + kOffBuf + fr * kFrame + kXBytes + (e - fr * 20) * 16), "r"(e - fr * 20 < 16 ? kPadStat : 0u) : "memory");
    asm volatile("fence.proxy.async.shared::cta;" ::: "memory");
  }
#pragma unroll
  for (int i = 0; i < PAD; i++) sched_fence(tid + i, 0, 0);
  __syncthreads();
  if (lane == 0 && wg < W0) tma_load(sb + kOffBuf + (tid >> 5) * kFrame, &tm, sb + kOffBar + wg * 8, b + wg * nb, wp);
  if (PL && lane == 0 && wg >= 2 && b < 48) tma_prefetch(&tm, nb - 48 + b + (wg - 2) * nb, wp);
  __syncwarp();
  asm volatile("griddepcontrol.wait;" ::: "memory");
  if (tid == 0) {
    if (!(WF & 1)) asm volatile("fence.proxy.async.global;" ::: "memory");
#pragma unroll
    for (int i = 0; i < 2; i++) {
      const uint32_t o = i ? kOffAs : 0, n = i ? kWBytes - kOffAs : kOffAs, bar = sb + kOffBarW + 8 * i;
      mbar_expect(bar, n);
      asm volatile("cp.async.bulk.shared::cluster.global.mbarrier::complete_tx::bytes [%0], [%1], %2, [%3];"
                   ::"r"(sb + o), "l"(reinterpret_cast<const uint8_t*>(g_wimg) + o), "r"(n), "r"(bar) : "memory");
    }
  }
  __syncwarp();
  if (wg >= W0) {
    if (WS && wg >= W1e) mbar_wait(sb + kOffBarW + (WS == 2 || (WS == 3 && wg == 3) ? 8 : 0), 0);
    if (lane == 0) tma_load(sb + kOffBuf + (tid >> 5) * kFrame, &tm, sb + kOffBar + wg * 8, b + wg * nb, wp);
    __syncwarp();
  }
  Params P;
  {
    const float4 p0 = __ldcg(reinterpret_cast<const float4*>(&g_par));
    P.cS_t = p0.x; P.cS_s = p0.y; P.kt = p0.z; P.kappa = p0.w;
    P.sgmin = fmaxf(0.0045f, P.kappa * 0.011f);
  }
  const bool scaled = __any_sync(0xffffffffu, P.cS_s != 1.f);
  const bool direct = __all_sync(0xffffffffu, (P.cS_t == 1.f) & (P.kt <= 256.f) & (P.kappa <= 16.f));
  const int widx = __popc(((ROLE >> wg) & 1 ? ROLE : ~ROLE) & ((1 << wg) - 1));
  const bool isT = (ROLE >> wg) & 1;
  if (isT) {
    loop_T(sb, nfull, widx, wp, lane, P, direct TRPASS(g_trace + (b * 16 + wg * 4 + wp) * 1024));
  } else {
    loop_S(sb, nfull, widx, wp, lane, P, scaled, &tm, out TRPASS(g_trace + (b * 16 + wg * 4 + wp) * 1024));
  }
}

__device__ __forceinline__ int ch_pos(int ch) { return 32 * (ch >> 5) + 4 * (ch & 4) + 8 * (ch & 1) + 2 * ((ch >> 3) & 3) + ((ch >> 1) & 1); }
__device__ __forceinline__ float pow2_ceil(float v) {
  return __uint_as_float((__float_as_uint(v) + 0x7fffffu) & 0x7f800000u);
}

constexpr int PU1 = PU == 0 ? 24 : PU, PU2 = PU == 0 ? 12 : PU > 4 ? 4 : PU, PU3 = PU == 0 ? 3 : 1;
constexpr int kPrepSplit = 12;
constexpr int kPrepThreads = 384;
__global__ void __launch_bounds__(kPrepThreads) swin_prep(const __nv_bfloat16* __restrict__ wqkv_t, const __nv_bfloat16* __restrict__ wo_t,
                                                          const __nv_bfloat16* __restrict__ wqkv_s, const __nv_bfloat16* __restrict__ wo_s) {
  asm volatile("griddepcontrol.launch_dependents;");
  if (blockIdx.x == 0 && threadIdx.x == 0) g_ctr = 0;
  __shared__ __align__(16) uint32_t raw[2][96][52];
  __shared__ __align__(16) uint32_t mu[3][52];
  __shared__ float nrm[12], nrm2[6], csum[6][9];
  const int mat = blockIdx.x / kPrepSplit, blk = blockIdx.x % kPrepSplit;
  const int tid = threadIdx.x, lane = tid & 31, warp = tid >> 5, g = lane >> 2, c = lane & 3;
  const __nv_bfloat16* wqkv = mat < 2 ? wqkv_t : wqkv_s;
  const __nv_bfloat16* wo = mat < 2 ? wo_t : wo_s;
  const bool isA = (mat & 1) == 0;
  {
    uint4 v[3], u[3];
#pragma unroll
    for (int q = 0; q < 3; q++) {
      const int e = tid + q * kPrepThreads, i = e / 12, c8 = (e % 12) * 8;
      v[q] = __ldg(reinterpret_cast<const uint4*>(wqkv + i * 288 + (isA ? 0 : 192) + c8));
      u[q] = __ldg(reinterpret_cast<const uint4*>(isA ? wqkv + i * 288 + 96 + c8 : wo + i * 96 + c8));
    }
#pragma unroll
    for (int q = 0; q < 3; q++) {
      const int e = tid + q * kPrepThreads, i = e / 12, c4 = (e % 12) * 4;
      *reinterpret_cast<uint4*>(&raw[0][i][c4]) = v[q];
      *reinterpret_cast<uint4*>(&raw[1][i][c4]) = u[q];
    }
  }
  __syncthreads();
  {
    const int m = warp / 6, cp = (warp % 6) * 8 + g;
    const bool rows = mat == 1 && m == 1;
    const uint32_t* src = rows ? &raw[1][2 * cp][c] : &raw[m][c][cp];
    const int st = rows ? 4 : 4 * 52, hop = rows ? 52 : 48 * 52;
    float s0 = 0.f, s1 = 0.f, q0 = 0.f, q1 = 0.f, s2 = 0.f, s3 = 0.f;
#pragma unroll
    for (int i = 0; i < 12; i++) {
      const uint32_t w = src[i * st], u = src[i * st + hop];
      const float lo = __uint_as_float(w << 16), hi = __uint_as_float(w & 0xffff0000u);
      const float l2 = __uint_as_float(u << 16), h2 = __uint_as_float(u & 0xffff0000u);
      s0 += lo; s1 += hi; s2 += l2; s3 += h2;
      q0 = fmaf(lo, lo, fmaf(l2, l2, q0)); q1 = fmaf(hi, hi, fmaf(h2, h2, q1));
    }
    { const float a = s0 + (rows ? s1 : s2), b = s3 + (rows ? s2 : s1); s0 = a; s1 = b; }
    s0 = quad_sum(s0) * (1.f / 96.f); s1 = quad_sum(s1) * (1.f / 96.f); q0 = quad_sum(q0); q1 = quad_sum(q1);
    if (m == 1 && c == 0) {
      const uint32_t hi = mat == 3 ? 0u : pack_bf2(s0, s1);
      mu[0][cp] = hi;
      mu[1][cp] = mat == 3 ? 0u : pack_bf2(s0 - __uint_as_float(hi << 16), s1 - __uint_as_float(hi & 0xffff0000u));
      mu[2][cp] = 0u;
    }
    if (m == 0 || isA) {
      q0 = fmaxf(fmaf(-96.f * s0, s0, q0), 0.f) + q0 * 1e-6f;
      q1 = fmaxf(fmaf(-96.f * s1, s1, q1), 0.f) + q1 * 1e-6f;
    }
    const bool usemax = m == 1 && mat == 3;
    float t = usemax ? fmaxf(q0, q1) : q0 + q1;
#pragma unroll
    for (int o = 4; o < 32; o <<= 1) { const float z = __shfl_xor_sync(0xffffffffu, t, o); t = usemax ? fmaxf(t, z) : t + z; }
    if (lane == 0) nrm[warp] = t;
  }
  __syncthreads();
  if (warp >= 6) return;
  float d[4] = {0.f, 0.f, 0.f, 0.f}, e[4] = {0.f, 0.f, 0.f, 0.f}, v0, v1;
  {
    const uint32_t arow = smem_u32(&raw[0][16 * warp + (lane & 15)][(lane >> 4) * 4]);
    const uint32_t brow = isA ? smem_u32(&raw[1][blk * 8 + (lane & 7)][(lane >> 3) * 4]) : smem_u32(&raw[1][lane][blk * 4]);
    const uint32_t mrow = smem_u32(&mu[min(lane & 7, 2)][(lane >> 3) * 4]);
#pragma unroll PU3
    for (int k2 = 0; k2 < 3; k2++) {
      uint32_t b[4], m[4];
      if (isA) ldsm4(b, brow + k2 * 64);
      else asm volatile("ldmatrix.sync.aligned.m8n8.x4.trans.shared.b16 {%0,%1,%2,%3}, [%4];"
                        : "=r"(b[0]), "=r"(b[1]), "=r"(b[2]), "=r"(b[3]) : "r"(brow + k2 * (32 * 208)) : "memory");
      ldsm4(m, mrow + k2 * 64);
#pragma unroll
      for (int hf = 0; hf < 2; hf++) {
        uint32_t a[4];
        ldsm4(a, arow + (2 * k2 + hf) * 32);
        asm volatile("mma.sync.aligned.m16n8k16.row.col.f32.bf16.bf16.f32 {%0,%1,%2,%3},{%4,%5,%6,%7},{%8,%9},{%0,%1,%2,%3};"
                     : "+f"(d[0]), "+f"(d[1]), "+f"(d[2]), "+f"(d[3])
                     : "r"(a[0]), "r"(a[1]), "r"(a[2]), "r"(a[3]), "r"(b[2 * hf]), "r"(b[2 * hf + 1]));
        asm volatile("mma.sync.aligned.m16n8k16.row.col.f32.bf16.bf16.f32 {%0,%1,%2,%3},{%4,%5,%6,%7},{%8,%9},{%0,%1,%2,%3};"
                     : "+f"(e[0]), "+f"(e[1]), "+f"(e[2]), "+f"(e[3])
                     : "r"(a[0]), "r"(a[1]), "r"(a[2]), "r"(a[3]), "r"(m[2 * hf]), "r"(m[2 * hf + 1]));
      }
    }
    v0 = __shfl_sync(0xffffffffu, e[0] + e[1], lane & ~3); v1 = __shfl_sync(0xffffffffu, e[2] + e[3], lane & ~3);
    d[0] -= v0; d[1] -= v0; d[2] -= v1; d[3] -= v1;
    float t0 = d[0] + d[2], t1 = d[1] + d[3], t2 = v0 + v1;
#pragma unroll
    for (int o = 4; o < 32; o <<= 1) {
      t0 += __shfl_xor_sync(0xffffffffu, t0, o); t1 += __shfl_xor_sync(0xffffffffu, t1, o); t2 += __shfl_xor_sync(0xffffffffu, t2, o);
    }
    if (g == 0) { csum[warp][2 * c] = t0; csum[warp][2 * c + 1] = t1; csum[warp][8] = t2; }
  }
  const float nl = nrm[0] + nrm[1] + nrm[2] + nrm[3] + nrm[4] + nrm[5];
  const float nr = mat == 3 ? fmaxf(fmaxf(fmaxf(nrm[6], nrm[7]), fmaxf(nrm[8], nrm[9])), fmaxf(nrm[10], nrm[11]))
                            : nrm[6] + nrm[7] + nrm[8] + nrm[9] + nrm[10] + nrm[11];
  const float bound = __fsqrt_rn(nl) * __fsqrt_rn(nr) * 1.01f;
  const float f = isA ? 0.14724448f : 1.f;
  float sc = pow2_ceil(fmaxf(bound * (isA ? 0.14724448f / 160.f : mat == 1 ? 1.f / 16.f : 1.f / 64.f), 1e-30f));
  if (isA) sc = fminf(fmaxf(sc, 1.f), 32768.f);
  const float mul = f * __uint_as_float(0x7f000000u - __float_as_uint(sc));
  if (blk == 0 && tid == 0) (mat == 0 ? g_par.cS_t : mat == 1 ? g_par.kt : mat == 2 ? g_par.cS_s : g_par.kappa) = sc;
  asm volatile("bar.sync 1, 192;" ::: "memory");
  float mean[2];
#pragma unroll
  for (int b = 0; b < 2; b++)
    mean[b] = (csum[0][2 * c + b] + csum[1][2 * c + b] + csum[2][2 * c + b] + csum[3][2 * c + b] + csum[4][2 * c + b] + csum[5][2 * c + b]) *
              (1.f / 96.f);
  uint8_t* img = reinterpret_cast<uint8_t*>(g_wimg) + (mat == 0 ? 0 : mat == 1 ? kOffWt : mat == 2 ? kOffAs : kOffWs);
  const float vmean = (csum[0][8] + csum[1][8] + csum[2][8] + csum[3][8] + csum[4][8] + csum[5][8]) * (1.f / 96.f);
  float off = 0.f;
  if (mat == 2) off = 1.5f * pow2_ceil(fmaxf(bound * mul * (3.f / 950.f), 1e-4f));
#pragma unroll
  for (int q = 0; q < 4; q++) {
    const int kp = ch_pos(16 * warp + g + 8 * (q >> 1)), np = ch_pos(blk * 8 + 2 * c + (q & 1));
    const uint32_t ko = (kp >> 5) * (mat == 0 ? kAtChunk : 6144) + (kp & 31) * 2;
    uint32_t a = ko + np * 64;
    a ^= ((a >> 7) & 3) << 4;
    float o = (d[q] - mean[q & 1]) * mul;
    o = mat == 2 ? o + off : __uint_as_float((__float_as_uint(o) + 0x8000u) & 0xffff0000u);
    *reinterpret_cast<__half*>(img + a) = __float2half_rn(o);
    if (mat == 1 && ((PP & 4) ? blk == q : blk == 0)) {
      a = (kp >> 5) * kAtChunk + (kp & 31) * 2 + (96 + 2 * c + (q & 1)) * 64;
      a ^= ((a >> 7) & 3) << 4;
      *reinterpret_cast<__half*>(reinterpret_cast<uint8_t*>(g_wimg) + a) = __float2half_rn((q & 1) ? ((q >> 1 ? v1 : v0) - vmean) * mul : 1.f / 96.f);
    }
  }
}

typedef CUresult (*EncodeFn)(CUtensorMap*, CUtensorMapDataType, cuuint32_t, void*, const cuuint64_t*, const cuuint64_t*,
                             const cuuint32_t*, const cuuint32_t*, CUtensorMapInterleave, CUtensorMapSwizzle,
                             CUtensorMapL2promotion, CUtensorMapFloatOOBfill);

}

extern "C" void kernel_launch(void* const* d_in, const int* in_sizes, int n_in, void* d_out, int out_size) {
  (void)in_sizes; (void)n_in; (void)out_size;
  static EncodeFn enc = nullptr;
  static int nsm = 0;
  if (!enc) {
    void* fn = nullptr;
    cudaDriverEntryPointQueryResult qr;
    cudaGetDriverEntryPoint("cuTensorMapEncodeTiled", &fn, cudaEnableDefault, &qr);
    enc = reinterpret_cast<EncodeFn>(fn);
    int dev = 0;
    cudaGetDevice(&dev);
    cudaDeviceGetAttribute(&nsm, cudaDevAttrMultiProcessorCount, dev);
    cudaFuncSetAttribute(swin_main, cudaFuncAttributeMaxDynamicSharedMemorySize, kSmemBytes);
  }
  Maps maps;
  CUtensorMap& tm = maps.tm;
  const cuuint64_t dims[5] = {32, kW, kH, kT, 3};
  const cuuint64_t strides[4] = {192, 192ull * kW, 192ull * kW * kH, 64};
  const cuuint32_t box[5] = {32, 7, 7, 1, 3};
  const cuuint32_t es[5] = {1, 1, 1, 1, 1};
  enc(&tm, CU_TENSOR_MAP_DATA_TYPE_BFLOAT16, 5, d_in[0], dims, strides, box, es, CU_TENSOR_MAP_INTERLEAVE_NONE,
      CU_TENSOR_MAP_SWIZZLE_64B, CU_TENSOR_MAP_L2_PROMOTION_L2_128B, CU_TENSOR_MAP_FLOAT_OOB_FILL_NONE);
  {
    const cuuint64_t d3[3] = {24 * kW, kH, kT};
    const cuuint64_t s3[2] = {192ull * kW, 192ull * kW * kH};
    const cuuint32_t b3[3] = {168, 7, 1};
    enc(&maps.pf, CU_TENSOR_MAP_DATA_TYPE_INT64, 3, d_in[0], d3, s3, b3, es, CU_TENSOR_MAP_INTERLEAVE_NONE,
        CU_TENSOR_MAP_SWIZZLE_NONE, (CUtensorMapL2promotion)PRM, CU_TENSOR_MAP_FLOAT_OOB_FILL_NONE);
  }

  cudaStream_t st = cudaStreamPerThread;
  swin_prep<<<4 * kPrepSplit, kPrepThreads, 0, st>>>(
      static_cast<const __nv_bfloat16*>(d_in[1]), static_cast<const __nv_bfloat16*>(d_in[2]),
      static_cast<const __nv_bfloat16*>(d_in[3]), static_cast<const __nv_bfloat16*>(d_in[4]));

  cudaLaunchConfig_t cfg = {};
  cfg.gridDim = dim3(nsm);
  cfg.blockDim = dim3(kNWG * 128);
  cfg.dynamicSmemBytes = kSmemBytes;
  cfg.stream = st;
  cudaLaunchAttribute at[1];
  at[0].id = cudaLaunchAttributeProgrammaticStreamSerialization;
  at[0].val.programmaticStreamSerializationAllowed = 1;
  cfg.attrs = at;
  cfg.numAttrs = 1;
  cudaLaunchKernelEx(&cfg, swin_main, maps, static_cast<uint8_t*>(d_out));
}
```

```cpp
#include <cuda_runtime.h>
#include <cuda.h>
#include <cuda_bf16.h>
#include <cuda_fp16.h>
#include <stdint.h>

#define LIKELY(x) __builtin_expect(!!(x), 1)
#define UNLIKELY(x) __builtin_expect(!!(x), 0)

namespace {

constexpr int kH = 511, kW = 511, kT = 4;
constexpr int kNWX = 73, kNWIN = 73 * 73;
constexpr int kChunk = 3136;
constexpr int kXBytes = 3 * kChunk;
constexpr int kFrame = 9728;
constexpr int kBufStride = 4 * kFrame;
constexpr int kWMat = 18432;
constexpr int kAtChunk = 104 * 64;
constexpr int kOffWt = 3 * kAtChunk;
constexpr int kOffAs = kOffWt + kWMat, kOffWs = kOffAs + kWMat;
constexpr int kWBytes = kOffWs + kWMat;
constexpr int kOffBuf = kWBytes;
constexpr int kOffBar = kOffBuf + 4 * kBufStride + 640;
constexpr int kOffFlag = kOffBar + 64;
constexpr int kOffBarW = kOffBar + 80;
constexpr int kOffBarB = kOffBar + 96;
constexpr int kOffCs = kOffBar + 128;
constexpr int kOffClaim = kOffBar + 132;
constexpr int kSmemBytes = kOffBar + 144;
constexpr int kNWG = 4;

struct Maps { CUtensorMap tm, pf; };
struct Params {
  float cS_t, cS_s;
  float kt;
  float kappa;
  float sgmin;
};

__device__ uint4 g_wimg[kWBytes / 16];
__device__ __align__(16) Params g_par;
__device__ uint32_t g_ctr;

__device__ __forceinline__ uint32_t smem_u32(const void* p) { return (uint32_t)__cvta_generic_to_shared(p); }
__device__ __forceinline__ void mbar_init(uint32_t a, int c) { asm volatile("mbarrier.init.shared::cta.b64 [%0], %1;" ::"r"(a), "r"(c)); }
__device__ __forceinline__ void mbar_expect(uint32_t a, int bytes) {
  asm volatile("mbarrier.arrive.expect_tx.shared::cta.b64 _, [%0], %1;" ::"r"(a), "r"(bytes) : "memory");
}
__device__ __forceinline__ void mbar_wait(uint32_t a, uint32_t par) {
  asm volatile(
      "{\n.reg .pred p;\n.reg .u32 n;\n"
      "mbarrier.try_wait.parity.shared::cta.b64 p, [%0], %1;\n"
      "@p bra.uni WDONE;\n"
      "mov.u32 n, 0;\n"
      "WLOOP:\n"
      "mbarrier.try_wait.parity.shared::cta.b64 p, [%0], %1;\n"
      "@p bra.uni WDONE;\n"
      "add.u32 n, n, 1;\n"
      "setp.lt.u32 p, n, 0x1000000;\n"
      "@p bra.uni WLOOP;\n"
      "trap;\n"
      "WDONE:\n}" ::"r"(a), "r"(par) : "memory");
}
__device__ __forceinline__ void tma_load(uint32_t dst, const CUtensorMap* m, uint32_t bar, uint32_t w, uint32_t t) {
  const uint32_t wy = (w * 57457u) >> 22, wx = w - wy * kNWX;
  mbar_expect(bar, kXBytes);
  asm volatile(
      "cp.async.bulk.tensor.5d.shared::cluster.global.mbarrier::complete_tx::bytes [%0], [%1, {%3,%4,%5,%6,%3}], [%2];" ::"r"(dst),
      "l"(m), "r"(bar), "r"(0), "r"(wx * 7), "r"(wy * 7), "r"(t)
      : "memory");
}
__device__ __forceinline__ void tma_prefetch(const CUtensorMap* m, uint32_t w, uint32_t t) {
  const uint32_t wy = (w * 57457u) >> 22, wx = w - wy * kNWX;
  asm volatile("cp.async.bulk.prefetch.tensor.3d.L2.global [%0, {%1,%2,%3}];" ::"l"(m + 1), "r"(wx * 168), "r"(wy * 7), "r"(t) : "memory");
}
__device__ __forceinline__ void wg_fence() { asm volatile("wgmma.fence.sync.aligned;" ::: "memory"); }
__device__ __forceinline__ void wg_commit() { asm volatile("wgmma.commit_group.sync.aligned;" ::: "memory"); }
template <int N>
__device__ __forceinline__ void wg_wait() { asm volatile("wgmma.wait_group.sync.aligned %0;" ::"n"(N) : "memory"); }
template <int N>
__device__ __forceinline__ void pin(uint32_t* d) {
#pragma unroll
  for (int i = 0; i < N; i++) asm volatile("" : "+r"(d[i])::"memory");
}
__device__ __forceinline__ void sched_fence(uint32_t a, uint32_t b, uint32_t c) {
  asm volatile("{\n.reg .pred p;\n.reg .b32 t;\nsetp.ne.u32 p, %0, 0x7fffffff;\n@p bra.uni SFD;\n"
               "add.u32 t, %1, %2;\nadd.u32 t, t, %3;\nnanosleep.u32 t;\nSFD:\n}" ::"r"(gridDim.x), "r"(a), "r"(b), "r"(c) : "memory");
}
__device__ __forceinline__ void hold(uint32_t sb, uint32_t v) {
  asm volatile("{\n.reg .pred p;\nsetp.eq.u32 p, %0, 0x7fffffff;\n@p st.volatile.shared.b32 [%1], %2;\n}" ::"r"(gridDim.x), "r"(sb), "r"(v) : "memory");
}
__device__ __forceinline__ uint64_t mk_desc(uint32_t addr, uint32_t lbo16) {
  return ((uint64_t)0x80000020u << 32) | ((addr >> 4) & 0x3fff) | (lbo16 << 16);
}
__device__ __forceinline__ uint64_t desc_at(uint32_t lo) { return ((uint64_t)0x80000020u << 32) | lo; }

#define R4(d, i) "+r"(d[i]), "+r"(d[i + 1]), "+r"(d[i + 2]), "+r"(d[i + 3])
#define O4(d, i) "=r"(d[i]), "=r"(d[i + 1]), "=r"(d[i + 2]), "=r"(d[i + 3])
#define D24 "{%0,%1,%2,%3,%4,%5,%6,%7,%8,%9,%10,%11,%12,%13,%14,%15,%16,%17,%18,%19,%20,%21,%22,%23},"
#define D14 "{%0,%1,%2,%3,%4,%5,%6,%7,%8,%9,%10,%11,%12,%13},"

template <int SC, int TB>
__device__ __forceinline__ void wg96h(uint32_t (&d)[24], const uint32_t* a, uint64_t db, uint32_t acc = 0) {
  if (SC == 2)
    asm volatile("{\n.reg .pred p;\nsetp.ne.u32 p, %30, 0;\n"
                 "wgmma.mma_async.sync.aligned.m64n96k16.f16.f16.f16 " D24 "{%24,%25,%26,%27}, %28, p, 1, 1, %29;\n}"
                 : R4(d, 0), R4(d, 4), R4(d, 8), R4(d, 12), R4(d, 16), R4(d, 20)
                 : "r"(a[0]), "r"(a[1]), "r"(a[2]), "r"(a[3]), "l"(db), "n"(TB), "r"(acc));
  else if (SC)
    asm volatile("wgmma.mma_async.sync.aligned.m64n96k16.f16.f16.f16 " D24 "{%24,%25,%26,%27}, %28, 1, 1, 1, %29;"
                 : R4(d, 0), R4(d, 4), R4(d, 8), R4(d, 12), R4(d, 16), R4(d, 20)
                 : "r"(a[0]), "r"(a[1]), "r"(a[2]), "r"(a[3]), "l"(db), "n"(TB));
  else
    asm volatile("wgmma.mma_async.sync.aligned.m64n96k16.f16.f16.f16 " D24 "{%24,%25,%26,%27}, %28, 0, 1, 1, %29;"
                 : O4(d, 0), O4(d, 4), O4(d, 8), O4(d, 12), O4(d, 16), O4(d, 20)
                 : "r"(a[0]), "r"(a[1]), "r"(a[2]), "r"(a[3]), "l"(db), "n"(TB));
}
template <int SC>
__device__ __forceinline__ void wg104h(uint32_t (&d)[26], const uint32_t* a, uint64_t db) {
  if (SC)
    asm volatile("wgmma.mma_async.sync.aligned.m64n104k16.f16.f16.f16 "
                 "{%0,%1,%2,%3,%4,%5,%6,%7,%8,%9,%10,%11,%12,%13,%14,%15,%16,%17,%18,%19,%20,%21,%22,%23,%24,%25},"
                 "{%26,%27,%28,%29}, %30, 1, 1, 1, 0;"
                 : R4(d, 0), R4(d, 4), R4(d, 8), R4(d, 12), R4(d, 16), R4(d, 20), "+r"(d[24]), "+r"(d[25])
                 : "r"(a[0]), "r"(a[1]), "r"(a[2]), "r"(a[3]), "l"(db));
  else
    asm volatile("wgmma.mma_async.sync.aligned.m64n104k16.f16.f16.f16 "
                 "{%0,%1,%2,%3,%4,%5,%6,%7,%8,%9,%10,%11,%12,%13,%14,%15,%16,%17,%18,%19,%20,%21,%22,%23,%24,%25},"
                 "{%26,%27,%28,%29}, %30, 0, 1, 1, 0;"
                 : O4(d, 0), O4(d, 4), O4(d, 8), O4(d, 12), O4(d, 16), O4(d, 20), "=r"(d[24]), "=r"(d[25])
                 : "r"(a[0]), "r"(a[1]), "r"(a[2]), "r"(a[3]), "l"(db));
}
template <int SC>
__device__ __forceinline__ void wg56h(uint32_t* d, const uint32_t* a, uint64_t db) {
  if (SC)
    asm volatile("wgmma.mma_async.sync.aligned.m64n56k16.f16.f16.f16 " D14 "{%14,%15,%16,%17}, %18, 1, 1, 1, 0;"
                 : R4(d, 0), R4(d, 4), R4(d, 8), "+r"(d[12]), "+r"(d[13])
                 : "r"(a[0]), "r"(a[1]), "r"(a[2]), "r"(a[3]), "l"(db));
  else
    asm volatile("wgmma.mma_async.sync.aligned.m64n56k16.f16.f16.f16 " D14 "{%14,%15,%16,%17}, %18, 0, 1, 1, 0;"
                 : O4(d, 0), O4(d, 4), O4(d, 8), "=r"(d[12]), "=r"(d[13])
                 : "r"(a[0]), "r"(a[1]), "r"(a[2]), "r"(a[3]), "l"(db));
}
template <int SC>
__device__ __forceinline__ void wg64h(uint32_t* d, const uint32_t* a, uint64_t db) {
  if (SC)
    asm volatile("wgmma.mma_async.sync.aligned.m64n64k16.f16.f16.f16 {%0,%1,%2,%3,%4,%5,%6,%7,%8,%9,%10,%11,%12,%13,%14,%15}, {%16,%17,%18,%19}, %20, 1, 1, 1, 0;"
                 : R4(d, 0), R4(d, 4), R4(d, 8), R4(d, 12)
                 : "r"(a[0]), "r"(a[1]), "r"(a[2]), "r"(a[3]), "l"(db));
  else
    asm volatile("wgmma.mma_async.sync.aligned.m64n64k16.f16.f16.f16 {%0,%1,%2,%3,%4,%5,%6,%7,%8,%9,%10,%11,%12,%13,%14,%15}, {%16,%17,%18,%19}, %20, 0, 1, 1, 0;"
                 : O4(d, 0), O4(d, 4), O4(d, 8), O4(d, 12)
                 : "r"(a[0]), "r"(a[1]), "r"(a[2]), "r"(a[3]), "l"(db));
}
template <int SC>
__device__ __forceinline__ void wg40h(uint32_t* d, const uint32_t* a, uint64_t db) {
  if (SC)
    asm volatile("wgmma.mma_async.sync.aligned.m64n40k16.f16.f16.f16 {%0,%1,%2,%3,%4,%5,%6,%7,%8,%9}, {%10,%11,%12,%13}, %14, 1, 1, 1, 0;"
                 : R4(d, 0), R4(d, 4), "+r"(d[8]), "+r"(d[9])
                 : "r"(a[0]), "r"(a[1]), "r"(a[2]), "r"(a[3]), "l"(db));
  else
    asm volatile("wgmma.mma_async.sync.aligned.m64n40k16.f16.f16.f16 {%0,%1,%2,%3,%4,%5,%6,%7,%8,%9}, {%10,%11,%12,%13}, %14, 0, 1, 1, 0;"
                 : O4(d, 0), O4(d, 4), "=r"(d[8]), "=r"(d[9])
                 : "r"(a[0]), "r"(a[1]), "r"(a[2]), "r"(a[3]), "l"(db));
}
template <int SC>
__device__ __forceinline__ void gemm_w(uint32_t (&d)[24], const uint32_t* a, uint64_t dw, uint32_t acc = 0) {
  wg_fence();
  wg96h<SC, 0>(d, a, dw, acc); wg96h<1, 0>(d, a + 4, dw + 2);
  wg96h<1, 0>(d, a + 8, dw + 384); wg96h<1, 0>(d, a + 12, dw + 386);
  wg96h<1, 0>(d, a + 16, dw + 768); wg96h<1, 0>(d, a + 20, dw + 770);
  wg_commit();
}
__device__ __forceinline__ void lds128(uint32_t* r, uint32_t a) {
  asm volatile("ld.shared.v4.b32 {%0,%1,%2,%3}, [%4];" : "=r"(r[0]), "=r"(r[1]), "=r"(r[2]), "=r"(r[3]) : "r"(a) : "memory");
}
__device__ __forceinline__ uint32_t lds32(uint32_t a) {
  uint32_t r; asm volatile("ld.volatile.shared.b32 %0, [%1];" : "=r"(r) : "r"(a) : "memory"); return r;
}
__device__ __forceinline__ void sts32(uint32_t a, uint32_t v) { asm volatile("st.volatile.shared.b32 [%0], %1;" ::"r"(a), "r"(v) : "memory"); }
__device__ __forceinline__ void ldsm4(uint32_t* r, uint32_t a) {
  asm volatile("ldmatrix.sync.aligned.m8n8.x4.shared.b16 {%0,%1,%2,%3}, [%4];"
               : "=r"(r[0]), "=r"(r[1]), "=r"(r[2]), "=r"(r[3]) : "r"(a) : "memory");
}
__device__ __forceinline__ void stsm4(uint32_t a, const uint32_t* r) {
  asm volatile("stmatrix.sync.aligned.m8n8.x4.shared.b16 [%0], {%1,%2,%3,%4};" ::"r"(a), "r"(r[0]), "r"(r[1]), "r"(r[2]), "r"(r[3])
               : "memory");
}
__device__ __forceinline__ uint32_t pack_h2(float lo, float hi) {
  uint32_t r; asm("cvt.rn.f16x2.f32 %0, %1, %2;" : "=r"(r) : "f"(hi), "f"(lo)); return r;
}
__device__ __forceinline__ uint32_t pack_h2_rz(float lo, float hi) {
  uint32_t r; asm("cvt.rz.f16x2.f32 %0, %1, %2;" : "=r"(r) : "f"(hi), "f"(lo)); return r;
}
__device__ __forceinline__ uint32_t pack_h2_sat(float lo, float hi) {
  uint32_t r; asm("cvt.rn.satfinite.f16x2.f32 %0, %1, %2;" : "=r"(r) : "f"(hi), "f"(lo)); return r;
}
__device__ __forceinline__ uint32_t pack_bf2(float lo, float hi) {
  uint32_t r; asm("cvt.rn.bf16x2.f32 %0, %1, %2;" : "=r"(r) : "f"(hi), "f"(lo)); return r;
}
__device__ __forceinline__ __half2 as_h2(uint32_t v) { return *reinterpret_cast<__half2*>(&v); }
__device__ __forceinline__ uint32_t as_u(__half2 v) { return *reinterpret_cast<uint32_t*>(&v); }
__device__ __forceinline__ float2 unpack_h2(uint32_t v) { return __half22float2(as_h2(v)); }
__device__ __forceinline__ uint32_t h2ex2(uint32_t v) { uint32_t r; asm("ex2.approx.f16x2 %0, %1;" : "=r"(r) : "r"(v)); return r; }
__device__ __forceinline__ uint32_t h2max(uint32_t a, uint32_t b) { return as_u(__hmax2(as_h2(a), as_h2(b))); }
__device__ __forceinline__ uint32_t h2add(uint32_t a, uint32_t b) { return as_u(__hadd2(as_h2(a), as_h2(b))); }
__device__ __forceinline__ uint32_t h2sub(uint32_t a, uint32_t b) { return as_u(__hsub2(as_h2(a), as_h2(b))); }
__device__ __forceinline__ uint32_t h2mul(uint32_t a, uint32_t b) { return as_u(__hmul2(as_h2(a), as_h2(b))); }
__device__ __forceinline__ uint32_t h2fma(uint32_t a, uint32_t b, uint32_t c) { return as_u(__hfma2(as_h2(a), as_h2(b), as_h2(c))); }
__device__ __forceinline__ uint32_t lo2(uint32_t v) { return as_u(__low2half2(as_h2(v))); }
__device__ __forceinline__ uint32_t hi2(uint32_t v) { return as_u(__high2half2(as_h2(v))); }
__device__ __forceinline__ uint32_t fold_add(uint32_t a, uint32_t b) { return h2add(__byte_perm(a, b, 0x5410), __byte_perm(a, b, 0x7632)); }
__device__ __forceinline__ uint32_t bitsel(uint32_t a, uint32_t m, uint32_t c) {
  uint32_t r; asm("lop3.b32 %0, %1, %2, %3, 0xe2;" : "=r"(r) : "r"(a), "r"(m), "r"(c)); return r;
}
__device__ __forceinline__ float rcp_fast(float v) { float r; asm("rcp.approx.ftz.f32 %0, %1;" : "=f"(r) : "f"(v)); return r; }
__device__ __forceinline__ float rsq_fast(float v) { float r; asm("rsqrt.approx.ftz.f32 %0, %1;" : "=f"(r) : "f"(v)); return r; }
__device__ __forceinline__ float quad_sum(float v) {
  v += __shfl_xor_sync(0xffffffffu, v, 1);
  return v + __shfl_xor_sync(0xffffffffu, v, 2);
}
__device__ __forceinline__ uint32_t quad_h2add(uint32_t v) {
  v = h2add(v, __shfl_xor_sync(0xffffffffu, v, 1));
  return h2add(v, __shfl_xor_sync(0xffffffffu, v, 2));
}
__device__ __forceinline__ uint32_t score_scale(const float* p) { const float v = __ldcg(p); return pack_h2(v, v); }

constexpr float kEps96 = 1e-5f * 96.f * 96.f;
__device__ __forceinline__ float2 stat_f32(uint32_t e) {
  const float2 h = unpack_h2(e);
  return make_float2((e & 0x8000u) ? __uint_as_float((e << 16) & 0x7fff0000u) : h.x, (e & 0x8000u) ? __uint_as_float(e & 0xffff0000u) : h.y);
}

__device__ __forceinline__ uint32_t swz(uint32_t a) { return a ^ ((a >> 3) & 0x30); }
__device__ __forceinline__ uint32_t prmt(uint32_t a, uint32_t b, uint32_t s) {
  uint32_t r; asm("prmt.b32 %0, %1, %2, %3;" : "=r"(r) : "r"(a), "r"(b), "r"(s)); return r;
}
struct A3 { uint32_t a[3]; };
__device__ __forceinline__ A3 swz3(uint32_t a) { return A3{{swz(a), swz(a + kChunk), swz(a + 2 * kChunk)}}; }
__device__ __forceinline__ void load_row(uint32_t* x, const A3& a, int t) {
  lds128(x, a.a[0] + t * kFrame); lds128(x + 4, a.a[1] + t * kFrame); lds128(x + 8, a.a[2] + t * kFrame);
}
__device__ __forceinline__ void row_to_h2(uint32_t* y, const uint32_t* x) {
#pragma unroll
  for (int j = 0; j < 12; j += 2) {
    y[2 * j] = pack_h2(__uint_as_float(x[j] << 16), __uint_as_float(x[j + 1] << 16));
    y[2 * j + 2] = pack_h2_rz(__uint_as_float(x[j]), __uint_as_float(x[j + 1])) & 0xfff8fff8u;
  }
}
__device__ __forceinline__ void gemm_at(uint32_t (&q)[26], const uint32_t* z, uint64_t da) {
  wg_fence();
  wg104h<0>(q, z, da); wg104h<1>(q, z + 4, da + 2);
  wg104h<1>(q, z + 8, da + 416); wg104h<1>(q, z + 12, da + 418);
  wg104h<1>(q, z + 16, da + 832); wg104h<1>(q, z + 20, da + 834);
  wg_commit();
}
__device__ __forceinline__ void gemm_at2(uint32_t (&q)[26], const uint32_t* z, uint64_t da) {
  wg_fence();
  wg64h<0>(q, z, da); wg40h<0>(q + 16, z, da + 256); wg64h<1>(q, z + 4, da + 2); wg40h<1>(q + 16, z + 4, da + 258);
  wg64h<1>(q, z + 8, da + 416); wg40h<1>(q + 16, z + 8, da + 672); wg64h<1>(q, z + 12, da + 418); wg40h<1>(q + 16, z + 12, da + 674);
  wg64h<1>(q, z + 16, da + 832); wg40h<1>(q + 16, z + 16, da + 1088); wg64h<1>(q, z + 20, da + 834); wg40h<1>(q + 16, z + 20, da + 1090);
  wg_commit();
}
template <int kChains>
__device__ __forceinline__ uint32_t sumsq(const uint32_t* z) {
  uint32_t q0[kChains], q1[kChains];
#pragma unroll
  for (int j = 0; j < 12; j++) {
    const uint32_t u = z[2 * j], v = z[2 * j + 1];
    q0[j % kChains] = j < kChains ? h2mul(u, u) : h2fma(u, u, q0[j % kChains]);
    q1[j % kChains] = j < kChains ? h2mul(v, v) : h2fma(v, v, q1[j % kChains]);
  }
  return kChains == 1 ? fold_add(q0[0], q1[0]) : fold_add(h2add(q0[0], q0[kChains - 1]), h2add(q1[0], q1[kChains - 1]));
}
__device__ __forceinline__ uint32_t scores(const uint32_t* q, const uint32_t* z, uint32_t selK) {
  uint32_t d[4];
#pragma unroll
  for (int j = 0; j < 12; j++) {
#pragma unroll
    for (int k = 0; k < 4; k++) d[k] = j ? h2fma(q[2 * j + (k >> 1)], z[2 * j + (k & 1)], d[k]) : h2mul(q[k >> 1], z[k & 1]);
  }
  const uint32_t e0 = fold_add(d[0], d[2]), e1 = fold_add(d[1], d[3]);
  return h2add(prmt(e0, e1, selK), __shfl_xor_sync(0xffffffffu, prmt(e0, e1, selK ^ 0x2222u), 1));
}
__device__ __forceinline__ float2 rstd(float2 d) { return make_float2(rsq_fast(fmaf(d.x, 1.f / 96.f, 1e-5f)), rsq_fast(fmaf(d.y, 1.f / 96.f, 1e-5f))); }
__device__ __forceinline__ void ln1_f32(uint32_t* z, const A3& la, int t, float* ie, float* m) {
  float acc[48];
  uint32_t x0[12], x1[12];
  load_row(x0, la, t); load_row(x1, la, t + 1);
#pragma unroll
  for (int j = 0; j < 12; j++) {
    acc[4 * j] = __uint_as_float(x0[j] << 16); acc[4 * j + 1] = __uint_as_float(x0[j] & 0xffff0000u);
    acc[4 * j + 2] = __uint_as_float(x1[j] << 16); acc[4 * j + 3] = __uint_as_float(x1[j] & 0xffff0000u);
  }
  float s[4], q[4];
#pragma unroll
  for (int e = 0; e < 4; e++) { s[e] = acc[e]; q[e] = acc[e] * acc[e]; }
#pragma unroll
  for (int j = 4; j < 48; j++) { s[j & 3] += acc[j]; q[j & 3] = fmaf(acc[j], acc[j], q[j & 3]); }
  const float s0 = quad_sum(s[0] + s[1]), s1 = quad_sum(s[2] + s[3]), q0 = quad_sum(q[0] + q[1]), q1 = quad_sum(q[2] + q[3]);
  const float u0 = rsq_fast(fmaxf(fmaf(-s0, s0, fmaf(q0, 96.f, kEps96)), kEps96));
  const float u1 = rsq_fast(fmaxf(fmaf(-s1, s1, fmaf(q1, 96.f, kEps96)), kEps96));
  const float n0 = -s0 * u0, n1 = -s1 * u1;
  ie[0] = 96.f * u0; ie[1] = 96.f * u1;
  m[0] = s0 * (1.f / 96.f); m[1] = s1 * (1.f / 96.f);
#pragma unroll
  for (int j = 0; j < 12; j++) {
    const int e = 4 * (j & ~1) + (j & 1);
    z[2 * j] = pack_h2(fmaf(acc[e], ie[0], n0), fmaf(acc[e + 4], ie[0], n0));
    z[2 * j + 1] = pack_h2(fmaf(acc[e + 2], ie[1], n1), fmaf(acc[e + 6], ie[1], n1));
  }
}
__device__ __forceinline__ float2 sumsq_f32(const uint32_t* z) {
  float2 qq = make_float2(0.f, 0.f);
#pragma unroll
  for (int j = 0; j < 12; j++) {
    const float2 u = unpack_h2(z[2 * j]), v = unpack_h2(z[2 * j + 1]);
    qq.x = fmaf(u.x, u.x, fmaf(u.y, u.y, qq.x)); qq.y = fmaf(v.x, v.x, fmaf(v.y, v.y, qq.y));
  }
  return make_float2(quad_sum(qq.x), quad_sum(qq.y));
}
__device__ __forceinline__ float2 var96_f32(const uint32_t* z, uint32_t my) {
  const float2 q = sumsq_f32(z), m = unpack_h2(my);
  return make_float2(fmaf(-96.f * m.x, m.x, q.x), fmaf(-96.f * m.y, m.y, q.y));
}
__device__ __forceinline__ void ln2(uint32_t* h, uint32_t rr, uint32_t my, const A3& ma, int t) {
  const uint32_t nn = as_u(__hmul2(__hneg2(as_h2(my)), as_h2(rr)));
#pragma unroll
  for (int j = 0; j < 12; j++) { h[2 * j] = h2fma(h[2 * j], lo2(rr), lo2(nn)); h[2 * j + 1] = h2fma(h[2 * j + 1], hi2(rr), hi2(nn)); }
#pragma unroll
  for (int k = 0; k < 3; k++) { stsm4(ma.a[k] + t * kFrame, h + 8 * k); stsm4((ma.a[k] ^ 32) + t * kFrame, h + 8 * k + 4); }
}


__device__ __forceinline__ uint32_t ring_pos(uint32_t r) { return min(r, r - 196u); }
__device__ __forceinline__ uint32_t ring_row(uint32_t r) { return ((r * 1338u) >> 16) * (kBufStride - kChunk) + r * 64; }
__device__ __forceinline__ uint32_t ring_stat(uint32_t r) { return ((r * 1338u) >> 16) * (kBufStride - 49 * 4) + r * 4; }
__device__ __forceinline__ A3 t_in_addr(uint32_t sb, uint32_t r0, int lane) {
  return swz3(sb + kOffBuf + (lane & 3) * 16 + ring_row(ring_pos(r0 + (lane >> 2))));
}
__device__ __forceinline__ A3 t_out_addr(uint32_t sb, uint32_t r0, int lane) {
  return swz3(sb + kOffBuf + ((lane >> 3) & 1) * kFrame + (lane & 16) + ring_row(ring_pos(r0 + (lane & 7))));
}
__device__ __forceinline__ uint32_t t_stat_addr(uint32_t sb, uint32_t r0, int lane) {
  return sb + kOffBuf + kXBytes + (lane & 3) * kFrame + ring_stat(ring_pos(r0 + (lane >> 2)));
}
__device__ __forceinline__ void t_release(uint32_t bar, uint32_t ia, uint32_t ib, int lane) {
  __syncwarp();
  asm volatile("{\n.reg .pred p;\nsetp.le.u32 p, %1, %2;\n@p mbarrier.arrive.shared::cta.b64 _, [%0];\n}"
               ::"r"(bar + ((ia + lane) & 3) * 8), "r"(lane), "r"(ib - ia) : "memory");
}
template <bool kDirect>
__device__ __forceinline__ void softmax4(uint32_t* s, uint32_t rhoA, uint32_t rhoB, uint32_t ro, float f) {
  if (kDirect) { s[0] = h2mul(s[0], rhoA); s[1] = h2mul(s[1], rhoB); }
  uint32_t mx = h2max(s[0], s[1]);
  mx = h2max(lo2(mx), hi2(mx));
  if (kDirect) {
    const uint32_t nm = as_u(__hmul2(__hneg2(as_h2(mx)), as_h2(ro)));
    s[0] = h2fma(s[0], ro, nm); s[1] = h2fma(s[1], ro, nm);
  } else {
    s[0] = h2mul(h2sub(s[0], mx), ro); s[1] = h2mul(h2sub(s[1], mx), ro);
  }
  s[0] = h2ex2(s[0]); s[1] = h2ex2(s[1]);
  uint32_t sm = h2add(s[0], s[1]);
  sm = h2add(lo2(sm), hi2(sm));
  const float iv = f * rcp_fast(__low2float(as_h2(sm)));
  const uint32_t inv = pack_h2(iv, iv);
  if (kDirect) { s[0] = h2mul(h2mul(s[0], rhoA), inv); s[1] = h2mul(h2mul(s[1], rhoB), inv); }
  else { s[0] = h2mul(s[0], inv); s[1] = h2mul(s[1], inv); }
}
template <bool kFirst>
__device__ __forceinline__ void mix(uint32_t* u, const uint32_t* z, uint32_t p0, uint32_t p1) {
#pragma unroll
  for (int j = 0; j < 12; j++) {
    u[2 * j] = h2fma(z[2 * j + 1], hi2(p0), kFirst ? h2mul(z[2 * j], lo2(p0)) : h2fma(z[2 * j], lo2(p0), u[2 * j]));
    u[2 * j + 1] = h2fma(z[2 * j + 1], hi2(p1), kFirst ? h2mul(z[2 * j], lo2(p1)) : h2fma(z[2 * j], lo2(p1), u[2 * j + 1]));
  }
}
template <bool kDirect>
__device__ __forceinline__ void put_stats(uint32_t sa, float sg, float mm, const Params& P) {
  const bool ok = (sg >= P.sgmin) & (kDirect || fmaf(sg, 9.8f, fabsf(mm)) < fmaf(P.kappa, -627.2f, 60000.f));
  const uint32_t sh = pack_h2(sg, mm), sw = pack_bf2(-sg, mm);
  asm volatile("st.shared.b32 [%0], %1;" ::"r"(sa), "r"(ok ? sh : sw) : "memory");
}

__device__ __forceinline__ bool task_T(uint32_t sb, uint32_t r0, uint32_t ia, uint32_t ib, uint32_t flag, int lane, const Params& P) {
  const int c = lane & 3;
  const uint32_t selK = (c & 1) ? 0x7632u : 0x5410u, selO = 0x1010u + c * 0x2222u;
  const uint64_t da = mk_desc(sb, 1), dw = mk_desc(sb + kOffWt, 1);
  uint32_t x[48], yA[24], yB[24], qA[26], qB[26], ssA, ssB;
  {
    const A3 la = t_in_addr(sb, r0, lane);
#pragma unroll
    for (int e = 0; e < 12; e++) {
      const int t = 2 * (e / 6) + (e & 1), k = (e % 6) >> 1, ep = e - 3, tp = 2 * (ep / 6) + (ep & 1), kp = (ep % 6) >> 1;
      if (ep >= 0) hold(sb, x[12 * tp + 4 * kp]);
      lds128(x + 12 * t + 4 * k, la.a[k] + t * kFrame);
    }
  }
  row_to_h2(yA, x); row_to_h2(yA + 1, x + 12);
  row_to_h2(yB, x + 24); row_to_h2(yB + 1, x + 36);
  ssB = sumsq<2>(yB);
  ssA = sumsq<2>(yA);
  gemm_at2(qA, yA, da);
  gemm_at(qB, yB, da);
  ssB = quad_h2add(ssB);
  ssA = quad_h2add(ssA);
  uint32_t rA[2], rB[2];
  wg_wait<1>(); pin<26>(qA);
  const uint32_t myA = __byte_perm(qA[24], qA[25], 0x5410), nuA = __byte_perm(qA[24], qA[25], 0x7632);
  const uint32_t nsA = h2mul(myA, 0xd600d600u);
  const float2 ra = rstd(unpack_h2(h2fma(nsA, myA, ssA)));
  const uint32_t rhoA = pack_h2(ra.x, ra.y);
  rA[0] = scores(qA, yA, selK);
  sched_fence(rA[0], rhoA, 0);
  wg_wait<0>(); pin<26>(qB);
  const uint32_t myB = __byte_perm(qB[24], qB[25], 0x5410), nuB = __byte_perm(qB[24], qB[25], 0x7632);
  const uint32_t nsB = h2mul(myB, 0xd600d600u);
  const float2 rb = rstd(unpack_h2(h2fma(nsB, myB, ssB)));
  const uint32_t rhoB = pack_h2(rb.x, rb.y);
  const uint32_t ro = prmt(rhoA, rhoB, selO), mo = bitsel(prmt(myA, myB, selO), 0xffffu, 0x292e0000u);
  asm volatile("{\n.reg .pred p, q;\n.reg .b32 t;\nabs.f16x2 t, %1;\nsetp.gtu.f16x2 p|q, t, %2;\nor.pred p, p, q;\n@p st.volatile.shared.b32 [%0], %2;\n}"
               ::"r"(flag), "r"(h2fma(ro, mo, 0xbc190000u)), "r"(0x3c003c00u) : "memory");
  uint32_t mu;
  rA[1] = scores(qA, yB, selK); rB[0] = scores(qB, yA, selK); rB[1] = scores(qB, yB, selK);
  uint32_t p[8], s[2];
#pragma unroll
  for (int k = 0; k < 2; k++) s[k] = h2add((c & 2) ? rB[k] : rA[k], __shfl_xor_sync(0xffffffffu, (c & 2) ? rA[k] : rB[k], 2));
  softmax4<true>(s, rhoA, rhoB, ro, P.kt);
#pragma unroll
  for (int t = 0; t < 4; t++) { p[2 * t] = __shfl_sync(0xffffffffu, s[0], t, 4); p[2 * t + 1] = __shfl_sync(0xffffffffu, s[1], t, 4); }
  mu = h2fma(s[1], nuB, h2mul(s[0], nuA));
  mix<true>(qA, yA, p[0], p[2]); mix<false>(qA, yB, p[1], p[3]);
  mu = h2add(lo2(mu), hi2(mu));
  mix<true>(qB, yA, p[4], p[6]);
  gemm_w<1>(yA, qA, dw);
  sched_fence(0, 0, 0);
  mix<false>(qB, yB, p[5], p[7]);
  gemm_w<1>(yB, qB, dw);
  const A3 ma = t_out_addr(sb, r0, lane);
  wg_wait<1>(); pin<24>(yA);
  uint32_t bad;
  asm volatile("ld.shared.b32 %0, [%1];" : "=r"(bad) : "r"(flag + (yA[0] & (gridDim.x == 0x7fffffffu))) : "memory");
  float2 d = unpack_h2(h2fma(nsA, myA, quad_h2add(sumsq<1>(yA))));
  if (UNLIKELY(__any_sync(0xffffffffu, !(d.x + d.y < 65000.f) | (bad != 0)))) {
    if (__any_sync(0xffffffffu, bad != 0)) {
      wg_wait<0>(); pin<24>(yB);
      return false;
    }
    d = var96_f32(yA, myA);
  }
  float2 r = rstd(make_float2(fabsf(d.x), fabsf(d.y)));
  const uint32_t rrA = pack_h2(r.x, r.y);
  ln2(yA, rrA, myA, ma, 0);
  t_release(sb + kOffBar + 32, ia, ib, lane);
  wg_wait<0>(); pin<24>(yB);
  d = unpack_h2(h2fma(nsB, myB, quad_h2add(sumsq<1>(yB))));
  if (UNLIKELY(__any_sync(0xffffffffu, !(d.x + d.y < 65000.f)))) d = var96_f32(yB, myB);
  r = rstd(make_float2(fabsf(d.x), fabsf(d.y)));
  const uint32_t rrB = pack_h2(r.x, r.y);
  ln2(yB, rrB, myB, ma, 2);
  put_stats<true>(t_stat_addr(sb, r0, lane), rcp_fast(__low2float(as_h2(prmt(rrA, rrB, selO)))), __low2float(as_h2(h2add(mo, mu))), P);
  return true;
}

__device__ __forceinline__ void task_T_general(uint32_t sb, uint32_t r0, const Params& P) {
  int lane;
  asm volatile("mov.u32 %0, %%laneid;" : "=r"(lane));
  const int c = lane & 3;
  const uint64_t da = mk_desc(sb, 1), dw = mk_desc(sb + kOffWt, 1);
  uint32_t yA[24], yB[24], qA[26], qB[26];
  float ieo, mo, ao;
  {
    float ie[4], m[4];
    const A3 la = t_in_addr(sb, r0, lane);
    ln1_f32(yA, la, 0, ie, m);
    ln1_f32(yB, la, 2, ie + 2, m + 2);
    const float2 na = sumsq_f32(yA), nb = sumsq_f32(yB);
    const float ik = 9.8f * rcp_fast(P.kt) * rsq_fast(fmaxf(fmaxf(fmaxf(na.x, na.y), fmaxf(nb.x, nb.y)), 2e-7f));
    ieo = (c & 2) ? ((c & 1) ? ie[3] : ie[2]) : ((c & 1) ? ie[1] : ie[0]);
    mo = (c & 2) ? ((c & 1) ? m[3] : m[2]) : ((c & 1) ? m[1] : m[0]);
    const bool lim = (ieo * P.kt > 400.f) & (ik < ieo);
    const float u = ik * rcp_fast(ieo);
    ao = lim ? u : 1.f; ieo = lim ? ik : ieo;
  }
  uint32_t rA[2], rB[2], s[2], p[8];
  const uint32_t selK = (c & 1) ? 0x7632u : 0x5410u;
  gemm_at(qA, yA, da);
  wg_wait<0>(); pin<26>(qA);
  const uint32_t nuA = __byte_perm(qA[24], qA[25], 0x7632);
  rA[0] = scores(qA, yA, selK); rA[1] = scores(qA, yB, selK);
  sched_fence(rA[0], rA[1], nuA);
  gemm_at(qB, yB, da);
  wg_wait<0>(); pin<26>(qB);
  const uint32_t nuB = __byte_perm(qB[24], qB[25], 0x7632);
  rB[0] = scores(qB, yA, selK); rB[1] = scores(qB, yB, selK);
#pragma unroll
  for (int k = 0; k < 2; k++) s[k] = h2add((c & 2) ? rB[k] : rA[k], __shfl_xor_sync(0xffffffffu, (c & 2) ? rA[k] : rB[k], 2));
  softmax4<false>(s, 0, 0, score_scale(&g_par.cS_t), P.kt * ieo);
  uint32_t mu = h2fma(s[1], nuB, h2mul(s[0], nuA));
  mu = h2add(lo2(mu), hi2(mu));
#pragma unroll
  for (int t = 0; t < 4; t++) { p[2 * t] = __shfl_sync(0xffffffffu, s[0], t, 4); p[2 * t + 1] = __shfl_sync(0xffffffffu, s[1], t, 4); }
  sched_fence(mu, 0, 0);
  mix<true>(qA, yA, p[0], p[2]); mix<false>(qA, yB, p[1], p[3]);
  mix<true>(qB, yA, p[4], p[6]); mix<false>(qB, yB, p[5], p[7]);
  const uint32_t ah = pack_h2(ao, ao);
#pragma unroll
  for (int t = 0; t < 4; t++) {
    const uint32_t a = __shfl_sync(0xffffffffu, ah, t, 4);
#pragma unroll
    for (int j = 0; j < 12; j++) asm volatile("mul.f16x2 %0, %0, %1;" : "+r"(((t & 2) ? yB : yA)[2 * j + (t & 1)]) : "r"(a));
  }
  gemm_w<1>(yA, qA, dw);
  gemm_w<1>(yB, qB, dw);
  wg_wait<0>(); pin<24>(yA); pin<24>(yB);
  asm volatile("mov.u32 %0, %%laneid;" : "=r"(lane));
  float ie[4];
#pragma unroll
  for (int t = 0; t < 4; t++) ie[t] = __shfl_sync(0xffffffffu, ieo, t, 4);
  const float2 da2 = sumsq_f32(yA), db2 = sumsq_f32(yB);
  const uint32_t rrA = pack_h2_sat(rsq_fast(fmaf(da2.x, 1.f / 96.f, 1e-5f * ie[0] * ie[0])), rsq_fast(fmaf(da2.y, 1.f / 96.f, 1e-5f * ie[1] * ie[1])));
  const uint32_t rrB = pack_h2_sat(rsq_fast(fmaf(db2.x, 1.f / 96.f, 1e-5f * ie[2] * ie[2])), rsq_fast(fmaf(db2.y, 1.f / 96.f, 1e-5f * ie[3] * ie[3])));
  const A3 ma = t_out_addr(sb, r0, lane);
  ln2(yA, rrA, 0u, ma, 0); ln2(yB, rrB, 0u, ma, 2);
  const float r = __low2float(as_h2(prmt(rrA, rrB, 0x1010u + (lane & 3) * 0x2222u))), sg = rcp_fast(r * ieo);
  put_stats<false>(t_stat_addr(sb, r0, lane), sg, fmaf(__low2float(as_h2(mu)) * r, sg, mo), P);
}

__device__ __forceinline__ void claim(uint32_t sb, uint32_t nfull) {
  const uint32_t nb = gridDim.x, nrem = kNWIN - nfull * nb;
  const uint32_t whole = max((int)(nrem * 25 / 49), (int)(2 * nrem - nb));
  uint32_t t;
  asm volatile("atom.relaxed.gpu.global.inc.u32 %0, [%1], 0x7fffffff;" : "=r"(t) : "l"(&g_ctr) : "memory");
  const uint32_t u = t - whole;
  sts32(sb + kOffClaim, t < whole ? (nfull * nb + t) | 0x10000u
                        : u < 2 * (nrem - whole) ? (nfull * nb + whole + (u >> 1)) | 0x50000u | ((u & 1) << 17)
                        : blockIdx.x + (nfull - 1) * nb);
}
__device__ __forceinline__ void loop_T(uint32_t sb, int nfull, int wg, int wp, int lane, const Params& P, bool direct) {
  const uint32_t barF = sb + kOffBar, barD = sb + kOffBarB, flag = sb + kOffFlag + wg * 4;
  mbar_wait(sb + kOffBarW, 0);
  uint32_t r0 = 32 * wg + 8 * wp, par = 0;
  int k = (49 * nfull + 63 - 32 * wg) >> 6;
  int kx = ((49 * nfull + 112 - 32 * wg) >> 6) - k;
  int kc = wg + wp ? 0 : k - ((49 * (nfull - 3) - 1) >> 6);
  for (;;) {
    if (UNLIKELY(k <= kc)) {
      if (k) {
        if (lane == 0) claim(sb, nfull);
        __syncwarp();
        kc = 0;
      } else {
        mbar_wait(barF + (nfull & 3) * 8, (nfull >> 2) & 1);
        k = __any_sync(0xffffffffu, lds32(sb + kOffClaim) & 0x10000u) ? kx : 0;
        kx = 0;
        if (k == 0) break;
      }
    }
    k--;
    const uint32_t ia = (r0 * 1338u) >> 16, ib = ((r0 + 7) * 1338u) >> 16;
    mbar_wait(barF + ia * 8, par);
    if (UNLIKELY(ib != ia)) mbar_wait(barF + (ib & 3) * 8, par ^ (ib >> 2));
    const uint32_t r = r0;
    r0 += 64;
    if (r0 >= 196) { r0 -= 196; par ^= 1; }
    if (LIKELY(direct)) {
      if (LIKELY(task_T(sb, r, ia, ib, flag, lane, P))) {
        t_release(barD, ia, ib, lane);
        continue;
      }
      asm volatile("barrier.cta.sync.aligned %0, 128;" ::"r"(wg + 1) : "memory");
      asm volatile("st.shared.b32 [%0], %1;\nfence.acq_rel.cta;" ::"r"(flag), "r"(0) : "memory");
    }
    task_T_general(sb, r, P);
    t_release(sb + kOffBar + 32, ia, ib, lane);
    t_release(barD, ia, ib, lane);
  }
}

struct SFrame {
  uint32_t oo;
  uint32_t t;
  uint32_t st;
  uint32_t d;
  bool light;
};
__device__ __forceinline__ SFrame s_frame(uint32_t sb, int t, int wp, int lane, A3& ma) {
  SFrame f;
  const int rb = (wp + t) & 3;
  f.light = rb == 3;
  f.t = t;
  f.d = ((sb + kOffBuf + t * kFrame) >> 4) & 0x3fff;
  f.st = t * kFrame + kXBytes + rb * 64;
  ma = swz3(t * kFrame + rb * 1024 + ((lane * 65) & 0x3d0));
  if (f.light && (lane & 15)) ma.a[0] = ma.a[1] = ma.a[2] = kXBytes + 256;
  const uint32_t r = 16 * rb + (lane >> 2);
  f.oo = (r + (r / 7) * (kW - 7)) * 12 + (lane & 3) + (((r + 8 + ((r + 8) / 7) * (kW - 7)) * 12 + (lane & 3)) << 16);
  asm volatile("" : "+r"(f.oo));
  return f;
}
template <int kRow>
__device__ __forceinline__ uint8_t* out_row(uint8_t* ob, const SFrame& f) {
  uint32_t o = f.oo;
  asm volatile("" : "+r"(o));
  uint8_t* r;
  asm("mad.wide.u32 %0, %1, 16, %2;" : "=l"(r) : "r"(kRow ? o >> 16 : o & 0xffffu), "l"(ob));
  return r;
}
template <int kHi, int kFrom = 0, int kTo = 6>
__device__ __forceinline__ void s_load(uint32_t (&v)[24], uint32_t buf, A3 ma) {
  asm volatile("" : "+r"(ma.a[0]), "+r"(ma.a[1]), "+r"(ma.a[2]));
#pragma unroll
  for (int e = kFrom; e < kTo; e++) {
    const uint32_t a = kHi ? ma.a[e >> 1] >> 16 : ma.a[e >> 1] & 0xffffu;
    ldsm4(v + 4 * e, buf + ((e & 1) ? a ^ 32 : a));
  }
}
__device__ __forceinline__ void gemm_s(uint32_t* s, const uint32_t* q, uint64_t dA) {
  wg_fence();
  wg56h<0>(s, q, dA); wg56h<1>(s, q + 4, dA + 2);
  wg56h<1>(s, q + 8, dA + 196); wg56h<1>(s, q + 12, dA + 198);
  wg56h<1>(s, q + 16, dA + 392); wg56h<1>(s, q + 20, dA + 394);
  wg_commit();
}
template <bool kAll>
__device__ __forceinline__ void stg128(uint8_t* o, const uint32_t* w, uint32_t doit) {
  if (kAll) asm volatile("st.global.v4.b32 [%0], {%1,%2,%3,%4};" ::"l"(o), "r"(w[0]), "r"(w[1]), "r"(w[2]), "r"(w[3]) : "memory");
  else asm volatile("{\n.reg .pred p;\nsetp.ne.u32 p, %5, 0;\n@p st.global.v4.b32 [%0], {%1,%2,%3,%4};\n}" ::"l"(o), "r"(w[0]), "r"(w[1]), "r"(w[2]), "r"(w[3]), "r"(doit) : "memory");
}
template <int kRow, bool kAll>
__device__ __forceinline__ void s_store(const uint32_t (&v)[24], uint32_t e, uint8_t* o) {
  uint32_t w[12];
#pragma unroll
  for (int j = 0; j < 12; j += 2) {
    const float2 y = unpack_h2(h2fma(v[2 * j + kRow], lo2(e), hi2(e))), z = unpack_h2(h2fma(v[2 * j + 2 + kRow], lo2(e), hi2(e)));
    w[j] = pack_bf2(y.x, z.x); w[j + 1] = pack_bf2(y.y, z.y);
  }
#pragma unroll
  for (int i3 = 0; i3 < 3; i3++) stg128<kAll>(o + 64 * i3, w + 4 * i3, e);
}
template <int kRow, bool kAdd>
__device__ __forceinline__ void s_store_wide(const uint32_t (&v)[24], uint32_t e, uint8_t* o, const Params& P) {
  const float2 z = stat_f32(e);
#pragma unroll
  for (int i3 = 0; i3 < 3; i3++) {
    uint32_t w[4] = {0, 0, 0, 0};
    if (kAdd)
      asm volatile("{\n.reg .pred p;\nsetp.ne.u32 p, %5, 0;\n@p ld.global.v4.b32 {%0,%1,%2,%3}, [%4];\n}"
                   : "+r"(w[0]), "+r"(w[1]), "+r"(w[2]), "+r"(w[3]) : "l"(o + 64 * i3), "r"(e) : "memory");
#pragma unroll
    for (int j = 0; j < 4; j++) {
      const float2 ya = unpack_h2(v[8 * i3 + 2 * (j & 2) + kRow]), yb = unpack_h2(v[8 * i3 + 2 * (j & 2) + 2 + kRow]);
      const float2 y = (j & 1) ? make_float2(ya.y, yb.y) : make_float2(ya.x, yb.x);
      w[j] = kAdd ? pack_bf2(fmaf(y.x, P.kappa, __uint_as_float(w[j] << 16)), fmaf(y.y, P.kappa, __uint_as_float(w[j] & 0xffff0000u)))
                  : pack_bf2(fmaf(y.x, z.x, z.y), fmaf(y.y, z.x, z.y));
    }
    stg128<false>(o + 64 * i3, w, e);
  }
  __syncwarp();
}
__device__ __forceinline__ uint32_t ex2_pair(uint32_t s, uint32_t sel) {
  uint32_t lo, hi;
  asm volatile("{\n.reg .b16 a, b, c;\nmov.b32 {a, b}, %2;\nex2.approx.f16 c, a;\ncvt.u32.u16 %0, c;\nex2.approx.f16 c, b;\ncvt.u32.u16 %1, c;\n}"
               : "=r"(lo), "=r"(hi) : "r"(s));
  return prmt(lo, hi, sel);
}
__device__ __forceinline__ uint32_t ex2_lo(uint32_t s, uint32_t sel) {
  uint32_t lo;
  asm volatile("{\n.reg .b16 a, b, c;\nmov.b32 {a, b}, %1;\nex2.approx.f16 c, a;\ncvt.u32.u16 %0, c;\n}" : "=r"(lo) : "r"(s));
  return prmt(lo, 0, sel);
}

__device__ __forceinline__ void turn_wait(uint32_t j) { asm volatile("barrier.cta.sync.aligned %0, 256;" ::"r"(5 + j) : "memory"); }
__device__ __forceinline__ void turn_pass(uint32_t j) { asm volatile("barrier.cta.arrive.aligned %0, 256;" ::"r"(6 - j) : "memory"); }

template <int kSecond>
__device__ __forceinline__ void step_S(uint32_t sb, uint32_t (&v)[24], uint32_t (&vn)[24], uint32_t (&q)[24], uint32_t (&s)[16], const SFrame& f,
                                       const SFrame& fn, const A3& ma, uint32_t i, uint32_t nfull, uint32_t w4, uint32_t& cl, uint8_t* ob, int lane,
                                       const Params& P, bool scaled, const CUtensorMap* tm) {
  const uint32_t ia = i & 3, ib = kSecond ? (i + 1) & 3 : ia;
  const uint32_t buf = sb + kOffBuf + ia * kBufStride, bufn = sb + kOffBuf + ib * kBufStride;
  const uint32_t never = gridDim.x == 0x7fffffffu;
  const uint64_t dQ = mk_desc(sb + kOffAs, 1), dW = dQ + ((i + kSecond) & never) + (kWMat >> 4);
  uint32_t p[16], u[24], e0, e1;
  ob += f.t * (kH * kW * 192u);
  const uint32_t nw = nfull + ((cl >> 16) & 1);
  asm volatile("" : "+l"(ob));
  const uint32_t sta = buf + f.st + (lane & 0x1c);
  asm volatile("ld.shared.b32 %0, [%1];" : "=r"(e0) : "r"(sta) : "memory");
  asm volatile("ld.shared.b32 %0, [%1];" : "=r"(e1) : "r"(sta + 32) : "memory");
  const uint32_t keep = (lane & 3) == 0 ? 0x0000ffffu : 0u;
  const bool pad0 = f.light && lane >= 4, pad1 = f.light;
  const uint32_t sel0 = pad0 ? 0x3232u : 0x5410u, sel1 = pad1 ? 0x3232u : 0x5410u;
  s[12] = bitsel(s[12], keep, 0xfc00fc00u); s[13] = bitsel(s[13], keep, 0xfc00fc00u);
  const uint32_t x0 = h2max(h2max(h2max(h2max(s[0], s[2]), s[4]), h2max(h2max(s[6], s[8]), s[10])), s[12]);
  const uint32_t x1 = h2max(h2max(h2max(h2max(s[1], s[3]), s[5]), h2max(h2max(s[7], s[9]), s[11])), s[13]);
  uint32_t okv;
  asm("{\n.reg .pred p, q;\nsetp.le.f16x2 p|q, %1, %2;\nand.pred p, p, q;\nselp.u32 %0, 1, 0, p;\n}"
      : "=r"(okv) : "r"(as_u(__hmax2(__habs2(as_h2(x0)), __habs2(as_h2(x1))))), "r"(0x47004700u));
  const bool ok = (okv != 0) & !scaled;
  p[12] = ex2_lo(s[12], sel0); p[13] = ex2_lo(s[13], sel1);
#pragma unroll
  for (int j = 0; j < 4; j++) p[j] = ex2_pair(s[j], (j & 1) ? sel1 : sel0);
  if (UNLIKELY(!__all_sync(0xffffffffu, ok))) {
    uint32_t mx = h2max(__byte_perm(x0, x1, 0x5410), __byte_perm(x0, x1, 0x7632));
    mx = h2max(mx, __shfl_xor_sync(0xffffffffu, mx, 1));
    mx = h2max(mx, __shfl_xor_sync(0xffffffffu, mx, 2));
    const uint32_t cs = lds32(sb + kOffCs);
#pragma unroll
    for (int j = 0; j < 7; j++) { s[2 * j] = h2mul(h2sub(s[2 * j], lo2(mx)), cs); s[2 * j + 1] = h2mul(h2sub(s[2 * j + 1], hi2(mx)), cs); }
    p[12] = ex2_lo(s[12], sel0); p[13] = ex2_lo(s[13], sel1);
#pragma unroll
    for (int j = 0; j < 4; j++) p[j] = ex2_pair(s[j], (j & 1) ? sel1 : sel0);
  }
  asm volatile("mov.b32 %0, 0;\nmov.b32 %1, 0;" : "=r"(p[14]), "=r"(p[15]));
  const uint64_t mn = desc_at(f.d + ia * (kBufStride >> 4) + (kChunk >> 4 << 16));
  wg_fence();
  wg96h<2, 1>(q, p + 12, mn + 192, never); wg96h<1, 1>(q, p, mn);
#pragma unroll
  for (int j = 4; j < 12; j++) p[j] = ex2_pair(s[j], (j & 1) ? sel1 : sel0);
  uint32_t wf;
  asm("lop3.b32 %0, %1, %2, 0x8000, 0xa8;" : "=r"(wf) : "r"(e0), "r"(e1));
  const bool wide = __any_sync(0xffffffffu, wf != 0u);
  uint32_t rs = fold_add(h2add(h2add(h2add(h2add(h2add(p[0], p[2]), p[12]), h2add(p[4], p[6])), p[8]), p[10]),
                         h2add(h2add(h2add(h2add(h2add(p[1], p[3]), p[13]), h2add(p[5], p[7])), p[9]), p[11])), r1, r2, r3;
  asm volatile("shfl.sync.bfly.b32 %0, %1, 1, 31, 0xffffffff;" : "=r"(r1) : "r"(rs));
  asm volatile("shfl.sync.bfly.b32 %0, %1, 2, 31, 0xffffffff;" : "=r"(r2) : "r"(rs));
  asm volatile("shfl.sync.bfly.b32 %0, %1, 3, 31, 0xffffffff;" : "=r"(r3) : "r"(rs));
  wg_fence();
  wg96h<1, 1>(q, p + 4, mn + 64); wg96h<1, 1>(q, p + 8, mn + 128);
  wg_commit();
  float g0 = __low2float(as_h2(e0)), g1 = __low2float(as_h2(e1));
  if (UNLIKELY(wide)) {
    s_store_wide<0, false>(v, e0, out_row<0>(ob, f), P); s_store_wide<1, false>(v, e1, out_row<1>(ob, f), P);
    asm volatile("mov.b32 %0, %2;\nmov.b32 %1, %2;" : "=f"(g0), "=f"(g1) : "f"(P.kappa));
    r1 += never; r2 += never;
  }
  rs = h2add(rs, r1);
  r1 = h2add(r2, r3);
  if (kSecond && i + 1 < nw) mbar_wait(sb + kOffBar + 32 + ib * 8, ((i + 1) >> 2) & 1);
  s_load<!kSecond, 0, 4>(vn, bufn, ma);
  rs = h2add(rs, r1);
  const float d0 = __low2float(as_h2(rs)), d1 = __high2float(as_h2(rs));
  const float c0 = P.kappa * rcp_fast(d0 * g0), c1 = P.kappa * rcp_fast(d1 * g1);
  const uint32_t cb = pack_h2_sat(c0, c1);
  turn_wait(f.t & 1);
  wg_wait<0>(); pin<24>(q);
#pragma unroll
  for (int j = 0; j < 12; j++) { u[2 * j] = h2mul(q[2 * j], lo2(cb)); u[2 * j + 1] = h2mul(q[2 * j + 1], hi2(cb)); }
  gemm_w<2>(v, u, dW, !wide);
  s_load<!kSecond, 4, 6>(vn, bufn, ma);
  gemm_w<2>(q, vn, dQ, never);
  if (f.light) {
    const uint32_t bar = sb + kOffBar + ia * 8;
    if (lane == 0) {
      const uint32_t c = i + 4 >= nfull ? cl : w4;
      if (i + 4 <= nw) {
        tma_load(buf + f.t * kFrame, tm, bar, c & 0xffffu, f.t ^ ((c >> 16) & 2));
        if (!kSecond) tma_prefetch(tm, c & 0xffffu, fn.t ^ ((c >> 16) & 2));
      }
    }
    __syncwarp();
  }
  if (kSecond && i + 1 < nw) mbar_wait(sb + kOffBarB + ib * 8, ((i + 1) >> 2) & 1);
  if (kSecond && UNLIKELY(i + 5 == nfull)) cl = __shfl_sync(0xffffffffu, lds32(sb + kOffClaim), 0);
  const bool plain = !(wide | f.light);
  wg_wait<1>(); pin<24>(v);
  if (kSecond) asm volatile("fence.proxy.async.shared::cta;" ::: "memory");
  if (LIKELY(plain)) s_store<0, true>(v, e0, out_row<0>(ob, f));
  wg_wait<0>(); pin<24>(q);
  gemm_s(s, q, desc_at(fn.d + ib * (kBufStride >> 4) + (1 << 16)));
  turn_pass(f.t & 1);
  if (LIKELY(plain)) s_store<1, true>(v, e1, out_row<1>(ob, f));
  else if (!wide) { s_store<0, false>(v, e0, out_row<0>(ob, f)); __syncwarp(); }
  else { s_store_wide<0, true>(v, e0, out_row<0>(ob, f), P); s_store_wide<1, true>(v, e1, out_row<1>(ob, f), P); }
  wg_wait<0>(); pin<14>(s);
}

__device__ __forceinline__ void loop_S(uint32_t sb, uint32_t nfull, int t0, int wp, int lane, const Params& P, bool scaled,
                                       const CUtensorMap* tm, uint8_t* __restrict__ out) {
  A3 ma, mb;
  const SFrame f0 = s_frame(sb, t0, wp, lane, ma), f1 = s_frame(sb, t0 + 2, wp, lane, mb);
#pragma unroll
  for (int k = 0; k < 3; k++) ma.a[k] += mb.a[k] << 16;
  uint32_t v0[24], v1[24], q[24], s[16];
  sts32(sb + kOffCs, pack_h2(P.cS_s, P.cS_s));
  mbar_wait(sb + kOffBar + 32, 0);
  s_load<0>(v0, sb + kOffBuf, ma);
  gemm_w<0>(q, v0, mk_desc(sb + kOffAs, 1));
  mbar_wait(sb + kOffBarB, 0);
  asm volatile("fence.proxy.async.shared::cta;" ::: "memory");
  wg_wait<0>(); pin<24>(q);
  gemm_s(s, q, mk_desc(sb + kOffBuf + f0.t * kFrame, 1));
  wg_wait<0>(); pin<14>(s);
  if (t0 == 1) turn_pass(t0);
  uint32_t cl = 0, w0 = blockIdx.x;
  for (uint32_t i = 0;; i++, w0 += gridDim.x) {
    const bool more = i + 1 < nfull + ((cl >> 16) & 1);
    const uint32_t c = i == nfull ? cl : w0, w = c & 0xffffu;
    const uint32_t wy = (w * 57457u) >> 22;
    uint8_t* ob = out + (size_t)((wy * (7 * kW - 7 * kNWX) + w * 7 + ((c >> 16) & 2) * (kH * kW)) * 192u);
    asm volatile("" : "+l"(ob));
    step_S<0>(sb, v0, v1, q, s, f0, f1, ma, i, nfull, w0 + 4 * gridDim.x, cl, ob, lane, P, scaled, tm);
    if (c & 0x40000u) break;
    step_S<1>(sb, v1, v0, q, s, f1, f0, ma, i, nfull, w0 + 4 * gridDim.x, cl, ob, lane, P, scaled, tm);
    if (!more) break;
  }
  if (t0 == 0) turn_wait(t0);
  const uint32_t nw = nfull + ((cl >> 16) & 1);
  mbar_wait(sb + kOffBar + (nw & 3) * 8, (nw >> 2) & 1);
}

__global__ void __launch_bounds__(kNWG * 128, 1) swin_main(const __grid_constant__ Maps maps, uint8_t* __restrict__ out) {
  const CUtensorMap& tm = maps.tm;
  extern __shared__ __align__(1024) uint8_t smem[];
  const uint32_t sb = smem_u32(smem);
  const int tid = threadIdx.x;
  const int wg = __shfl_sync(0xffffffffu, tid >> 7, 0);
  const int wp = __shfl_sync(0xffffffffu, (tid >> 5) & 3, 0);
  const int lane = tid & 31;
  const int b = blockIdx.x, nb = gridDim.x;
  const int nfull = kNWIN / nb;
  if (tid == 0) {
    if ((sb & 1023) || nfull < 8) __trap();
#pragma unroll
    for (int i = 0; i < 4; i++) {
      mbar_init(sb + kOffBar + i * 8, 4);
      mbar_init(sb + kOffBar + 32 + i * 8, 7);
      mbar_init(sb + kOffBarB + i * 8, 7);
    }
    asm volatile("st.shared.v4.b32 [%0], {%1,%1,%1,%1};" ::"r"(sb + kOffFlag), "r"(0) : "memory");
    mbar_init(sb + kOffBarW, 1); mbar_init(sb + kOffBarW + 8, 1);
    asm volatile("fence.mbarrier_init.release.cluster;" ::: "memory");
  }
  if (tid >= 128 && tid < 488) {
    const uint32_t e = tid - 128, fr = min(e / 20, 15u);
    asm volatile("st.shared.v4.b32 [%0], {%1,%1,%1,%1};" ::"r"(sb + kOffBuf + fr * kFrame + kXBytes + (e - fr * 20) * 16), "r"(0) : "memory");
    asm volatile("fence.proxy.async.shared::cta;" ::: "memory");
  }
  __syncthreads();
  if (lane == 0 && wg < 2) tma_load(sb + kOffBuf + (tid >> 5) * kFrame, &tm, sb + kOffBar + wg * 8, b + wg * nb, wp);
  __syncwarp();
  asm volatile("griddepcontrol.wait;" ::: "memory");
  if (tid == 0) {
#pragma unroll
    for (int i = 0; i < 2; i++) {
      const uint32_t o = i ? kOffAs : 0, n = i ? kWBytes - kOffAs : kOffAs, bar = sb + kOffBarW + 8 * i;
      mbar_expect(bar, n);
      asm volatile("cp.async.bulk.shared::cluster.global.mbarrier::complete_tx::bytes [%0], [%1], %2, [%3];"
                   ::"r"(sb + o), "l"(reinterpret_cast<const uint8_t*>(g_wimg) + o), "r"(n), "r"(bar) : "memory");
    }
  }
  __syncwarp();
  if (wg >= 2) {
    mbar_wait(sb + kOffBarW + 8, 0);
    if (lane == 0) tma_load(sb + kOffBuf + (tid >> 5) * kFrame, &tm, sb + kOffBar + wg * 8, b + wg * nb, wp);
    __syncwarp();
  }
  Params P;
  {
    const float4 p0 = __ldcg(reinterpret_cast<const float4*>(&g_par));
    P.cS_t = p0.x; P.cS_s = p0.y; P.kt = p0.z; P.kappa = p0.w;
    P.sgmin = fmaxf(0.0045f, P.kappa * 0.011f);
  }
  const bool scaled = __any_sync(0xffffffffu, P.cS_s != 1.f);
  const bool direct = __all_sync(0xffffffffu, (P.cS_t == 1.f) & (P.kt <= 256.f) & (P.kappa <= 16.f));
  if (wg < 2) loop_T(sb, nfull, wg, wp, lane, P, direct);
  else loop_S(sb, nfull, wg & 1, wp, lane, P, scaled, &tm, out);
}

__device__ __forceinline__ int ch_pos(int ch) { return 32 * (ch >> 5) + 4 * (ch & 4) + 8 * (ch & 1) + 2 * ((ch >> 3) & 3) + ((ch >> 1) & 1); }
__device__ __forceinline__ float pow2_ceil(float v) {
  return __uint_as_float((__float_as_uint(v) + 0x7fffffu) & 0x7f800000u);
}

constexpr int kPrepSplit = 12;
constexpr int kPrepThreads = 384;
__global__ void __launch_bounds__(kPrepThreads) swin_prep(const __nv_bfloat16* __restrict__ wqkv_t, const __nv_bfloat16* __restrict__ wo_t,
                                                          const __nv_bfloat16* __restrict__ wqkv_s, const __nv_bfloat16* __restrict__ wo_s) {
  asm volatile("griddepcontrol.launch_dependents;");
  if (blockIdx.x == 0 && threadIdx.x == 0) g_ctr = 0;
  __shared__ __align__(16) uint32_t raw[2][96][52];
  __shared__ __align__(16) uint32_t mu[3][52];
  __shared__ float nrm[12], csum[6][9];
  const int mat = blockIdx.x / kPrepSplit, blk = blockIdx.x % kPrepSplit;
  const int tid = threadIdx.x, lane = tid & 31, warp = tid >> 5, g = lane >> 2, c = lane & 3;
  const __nv_bfloat16* wqkv = mat < 2 ? wqkv_t : wqkv_s;
  const __nv_bfloat16* wo = mat < 2 ? wo_t : wo_s;
  const bool isA = (mat & 1) == 0;
  {
    uint4 v[3], u[3];
#pragma unroll
    for (int q = 0; q < 3; q++) {
      const int e = tid + q * kPrepThreads, i = e / 12, c8 = (e % 12) * 8;
      v[q] = __ldg(reinterpret_cast<const uint4*>(wqkv + i * 288 + (isA ? 0 : 192) + c8));
      u[q] = __ldg(reinterpret_cast<const uint4*>(isA ? wqkv + i * 288 + 96 + c8 : wo + i * 96 + c8));
    }
#pragma unroll
    for (int q = 0; q < 3; q++) {
      const int e = tid + q * kPrepThreads, i = e / 12, c4 = (e % 12) * 4;
      *reinterpret_cast<uint4*>(&raw[0][i][c4]) = v[q];
      *reinterpret_cast<uint4*>(&raw[1][i][c4]) = u[q];
    }
  }
  __syncthreads();
  {
    const int m = warp / 6, cp = (warp % 6) * 8 + g;
    const bool rows = mat == 1 && m == 1;
    const uint32_t* src = rows ? &raw[1][2 * cp][c] : &raw[m][c][cp];
    const int st = rows ? 4 : 4 * 52, hop = rows ? 52 : 48 * 52;
    float s0 = 0.f, s1 = 0.f, q0 = 0.f, q1 = 0.f, s2 = 0.f, s3 = 0.f;
#pragma unroll
    for (int i = 0; i < 12; i++) {
      const uint32_t w = src[i * st], u = src[i * st + hop];
      const float lo = __uint_as_float(w << 16), hi = __uint_as_float(w & 0xffff0000u);
      const float l2 = __uint_as_float(u << 16), h2 = __uint_as_float(u & 0xffff0000u);
      s0 += lo; s1 += hi; s2 += l2; s3 += h2;
      q0 = fmaf(lo, lo, fmaf(l2, l2, q0)); q1 = fmaf(hi, hi, fmaf(h2, h2, q1));
    }
    { const float a = s0 + (rows ? s1 : s2), b = s3 + (rows ? s2 : s1); s0 = a; s1 = b; }
    s0 = quad_sum(s0) * (1.f / 96.f); s1 = quad_sum(s1) * (1.f / 96.f); q0 = quad_sum(q0); q1 = quad_sum(q1);
    if (m == 1 && c == 0) {
      const uint32_t hi = mat == 3 ? 0u : pack_bf2(s0, s1);
      mu[0][cp] = hi;
      mu[1][cp] = mat == 3 ? 0u : pack_bf2(s0 - __uint_as_float(hi << 16), s1 - __uint_as_float(hi & 0xffff0000u));
      mu[2][cp] = 0u;
    }
    if (m == 0 || isA) {
      q0 = fmaxf(fmaf(-96.f * s0, s0, q0), 0.f) + q0 * 1e-6f;
      q1 = fmaxf(fmaf(-96.f * s1, s1, q1), 0.f) + q1 * 1e-6f;
    }
    const bool usemax = m == 1 && mat == 3;
    float t = usemax ? fmaxf(q0, q1) : q0 + q1;
#pragma unroll
    for (int o = 4; o < 32; o <<= 1) { const float z = __shfl_xor_sync(0xffffffffu, t, o); t = usemax ? fmaxf(t, z) : t + z; }
    if (lane == 0) nrm[warp] = t;
  }
  __syncthreads();
  if (warp >= 6) return;
  float d[4] = {0.f, 0.f, 0.f, 0.f}, e[4] = {0.f, 0.f, 0.f, 0.f}, v0, v1;
  {
    const uint32_t arow = smem_u32(&raw[0][16 * warp + (lane & 15)][(lane >> 4) * 4]);
    const uint32_t brow = isA ? smem_u32(&raw[1][blk * 8 + (lane & 7)][(lane >> 3) * 4]) : smem_u32(&raw[1][lane][blk * 4]);
    const uint32_t mrow = smem_u32(&mu[min(lane & 7, 2)][(lane >> 3) * 4]);
#pragma unroll
    for (int k2 = 0; k2 < 3; k2++) {
      uint32_t b[4], m[4];
      if (isA) ldsm4(b, brow + k2 * 64);
      else asm volatile("ldmatrix.sync.aligned.m8n8.x4.trans.shared.b16 {%0,%1,%2,%3}, [%4];"
                        : "=r"(b[0]), "=r"(b[1]), "=r"(b[2]), "=r"(b[3]) : "r"(brow + k2 * (32 * 208)) : "memory");
      ldsm4(m, mrow + k2 * 64);
#pragma unroll
      for (int hf = 0; hf < 2; hf++) {
        uint32_t a[4];
        ldsm4(a, arow + (2 * k2 + hf) * 32);
        asm volatile("mma.sync.aligned.m16n8k16.row.col.f32.bf16.bf16.f32 {%0,%1,%2,%3},{%4,%5,%6,%7},{%8,%9},{%0,%1,%2,%3};"
                     : "+f"(d[0]), "+f"(d[1]), "+f"(d[2]), "+f"(d[3])
                     : "r"(a[0]), "r"(a[1]), "r"(a[2]), "r"(a[3]), "r"(b[2 * hf]), "r"(b[2 * hf + 1]));
        asm volatile("mma.sync.aligned.m16n8k16.row.col.f32.bf16.bf16.f32 {%0,%1,%2,%3},{%4,%5,%6,%7},{%8,%9},{%0,%1,%2,%3};"
                     : "+f"(e[0]), "+f"(e[1]), "+f"(e[2]), "+f"(e[3])
                     : "r"(a[0]), "r"(a[1]), "r"(a[2]), "r"(a[3]), "r"(m[2 * hf]), "r"(m[2 * hf + 1]));
      }
    }
    v0 = __shfl_sync(0xffffffffu, e[0] + e[1], lane & ~3); v1 = __shfl_sync(0xffffffffu, e[2] + e[3], lane & ~3);
    d[0] -= v0; d[1] -= v0; d[2] -= v1; d[3] -= v1;
    float t0 = d[0] + d[2], t1 = d[1] + d[3], t2 = v0 + v1;
#pragma unroll
    for (int o = 4; o < 32; o <<= 1) {
      t0 += __shfl_xor_sync(0xffffffffu, t0, o); t1 += __shfl_xor_sync(0xffffffffu, t1, o); t2 += __shfl_xor_sync(0xffffffffu, t2, o);
    }
    if (g == 0) { csum[warp][2 * c] = t0; csum[warp][2 * c + 1] = t1; csum[warp][8] = t2; }
  }
  const float nl = nrm[0] + nrm[1] + nrm[2] + nrm[3] + nrm[4] + nrm[5];
  const float nr = mat == 3 ? fmaxf(fmaxf(fmaxf(nrm[6], nrm[7]), fmaxf(nrm[8], nrm[9])), fmaxf(nrm[10], nrm[11]))
                            : nrm[6] + nrm[7] + nrm[8] + nrm[9] + nrm[10] + nrm[11];
  const float bound = __fsqrt_rn(nl) * __fsqrt_rn(nr) * 1.01f;
  const float f = isA ? 0.14724448f : 1.f;
  float sc = pow2_ceil(fmaxf(bound * (isA ? 0.14724448f / 160.f : mat == 1 ? 1.f / 16.f : 1.f / 64.f), 1e-30f));
  if (isA) sc = fminf(fmaxf(sc, 1.f), 32768.f);
  const float mul = f * __uint_as_float(0x7f000000u - __float_as_uint(sc));
  if (blk == 0 && tid == 0) (mat == 0 ? g_par.cS_t : mat == 1 ? g_par.kt : mat == 2 ? g_par.cS_s : g_par.kappa) = sc;
  asm volatile("bar.sync 1, 192;" ::: "memory");
  float mean[2];
#pragma unroll
  for (int b = 0; b < 2; b++)
    mean[b] = (csum[0][2 * c + b] + csum[1][2 * c + b] + csum[2][2 * c + b] + csum[3][2 * c + b] + csum[4][2 * c + b] + csum[5][2 * c + b]) *
              (1.f / 96.f);
  uint8_t* img = reinterpret_cast<uint8_t*>(g_wimg) + (mat == 0 ? 0 : mat == 1 ? kOffWt : mat == 2 ? kOffAs : kOffWs);
  const float vmean = (csum[0][8] + csum[1][8] + csum[2][8] + csum[3][8] + csum[4][8] + csum[5][8]) * (1.f / 96.f);
  const float off = 1.5f * pow2_ceil(fmaxf(bound * mul * (3.f / 950.f), 1e-4f));
#pragma unroll
  for (int q = 0; q < 4; q++) {
    const int kp = ch_pos(16 * warp + g + 8 * (q >> 1)), np = ch_pos(blk * 8 + 2 * c + (q & 1));
    const uint32_t ko = (kp >> 5) * (mat == 0 ? kAtChunk : 6144) + (kp & 31) * 2;
    uint32_t a = ko + np * 64;
    a ^= ((a >> 7) & 3) << 4;
    float o = (d[q] - mean[q & 1]) * mul;
    o = mat == 2 ? o + off : __uint_as_float((__float_as_uint(o) + 0x8000u) & 0xffff0000u);
    *reinterpret_cast<__half*>(img + a) = __float2half_rn(o);
    if (mat == 1 && blk == q) {
      a = (kp >> 5) * kAtChunk + (kp & 31) * 2 + (96 + 2 * c + (q & 1)) * 64;
      a ^= ((a >> 7) & 3) << 4;
      *reinterpret_cast<__half*>(reinterpret_cast<uint8_t*>(g_wimg) + a) = __float2half_rn((q & 1) ? ((q >> 1 ? v1 : v0) - vmean) * mul : 1.f / 96.f);
    }
  }
}

typedef CUresult (*EncodeFn)(CUtensorMap*, CUtensorMapDataType, cuuint32_t, void*, const cuuint64_t*, const cuuint64_t*,
                             const cuuint32_t*, const cuuint32_t*, CUtensorMapInterleave, CUtensorMapSwizzle,
                             CUtensorMapL2promotion, CUtensorMapFloatOOBfill);

}

extern "C" void kernel_launch(void* const* d_in, const int* in_sizes, int n_in, void* d_out, int out_size) {
  (void)in_sizes; (void)n_in; (void)out_size;
  static EncodeFn enc = nullptr;
  static int nsm = 0;
  if (!enc) {
    void* fn = nullptr;
    cudaDriverEntryPointQueryResult qr;
    cudaGetDriverEntryPoint("cuTensorMapEncodeTiled", &fn, cudaEnableDefault, &qr);
    enc = reinterpret_cast<EncodeFn>(fn);
    int dev = 0;
    cudaGetDevice(&dev);
    cudaDeviceGetAttribute(&nsm, cudaDevAttrMultiProcessorCount, dev);
    cudaFuncSetAttribute(swin_main, cudaFuncAttributeMaxDynamicSharedMemorySize, kSmemBytes);
  }
  Maps maps;
  CUtensorMap& tm = maps.tm;
  const cuuint64_t dims[5] = {32, kW, kH, kT, 3};
  const cuuint64_t strides[4] = {192, 192ull * kW, 192ull * kW * kH, 64};
  const cuuint32_t box[5] = {32, 7, 7, 1, 3};
  const cuuint32_t es[5] = {1, 1, 1, 1, 1};
  enc(&tm, CU_TENSOR_MAP_DATA_TYPE_BFLOAT16, 5, d_in[0], dims, strides, box, es, CU_TENSOR_MAP_INTERLEAVE_NONE,
      CU_TENSOR_MAP_SWIZZLE_64B, CU_TENSOR_MAP_L2_PROMOTION_L2_128B, CU_TENSOR_MAP_FLOAT_OOB_FILL_NONE);
  {
    const cuuint64_t d3[3] = {24 * kW, kH, kT};
    const cuuint64_t s3[2] = {192ull * kW, 192ull * kW * kH};
    const cuuint32_t b3[3] = {168, 7, 1};
    enc(&maps.pf, CU_TENSOR_MAP_DATA_TYPE_INT64, 3, d_in[0], d3, s3, b3, es, CU_TENSOR_MAP_INTERLEAVE_NONE,
        CU_TENSOR_MAP_SWIZZLE_NONE, CU_TENSOR_MAP_L2_PROMOTION_L2_128B, CU_TENSOR_MAP_FLOAT_OOB_FILL_NONE);
  }

  cudaStream_t st = cudaStreamPerThread;
  swin_prep<<<4 * kPrepSplit, kPrepThreads, 0, st>>>(
      static_cast<const __nv_bfloat16*>(d_in[1]), static_cast<const __nv_bfloat16*>(d_in[2]),
      static_cast<const __nv_bfloat16*>(d_in[3]), static_cast<const __nv_bfloat16*>(d_in[4]));

  cudaLaunchConfig_t cfg = {};
  cfg.gridDim = dim3(nsm);
  cfg.blockDim = dim3(kNWG * 128);
  cfg.dynamicSmemBytes = kSmemBytes;
  cfg.stream = st;
  cudaLaunchAttribute at[1];
  at[0].id = cudaLaunchAttributeProgrammaticStreamSerialization;
  at[0].val.programmaticStreamSerializationAllowed = 1;
  cfg.attrs = at;
  cfg.numAttrs = 1;
  cudaLaunchKernelEx(&cfg, swin_main, maps, static_cast<uint8_t*>(d_out));
}
```
